```python
import torch

def _softmax(x, axis=-1):
    return torch.softmax(x, dim=axis)
def _gelu(x):
    return torch.nn.functional.gelu(x, approximate="tanh")
def _silu(x):
    return torch.nn.functional.silu(x)
def _sigmoid(x):
    return torch.sigmoid(x)
def _layernorm(x, axis=-1, eps=1e-5):
    m = x.mean(dim=axis, keepdim=True)
    v = x.var(dim=axis, keepdim=True, unbiased=False)
    return (x - m) / torch.sqrt(v + eps)
def _scatter_add(tgt, idx, src, axis=0):
    return tgt.clone().index_add_(axis, idx, src)
def _segment_sum(src, seg, n):
    out = torch.zeros((n,) + src.shape[1:], dtype=src.dtype)
    return out.index_add_(0, seg, src)
def _pad(x, pw):
    flat = tuple(v for pair in reversed(pw) for v in pair)
    return torch.nn.functional.pad(x, flat)

kernel_name = 'concat_heads__ssm_conv_h3__ssm_conv_s4__prompt'

def setup_inputs():

    _w = (lambda a: (lambda t: t.to(torch.bfloat16) if t.is_floating_point() else t)(torch.as_tensor(a)))
    def _A_setup():
        B, S, D = 1, 2048, 448
        ks = 4
        return {
            "q": _w((lambda *s: torch.randn(*s, dtype=torch.bfloat16) * 0.05)(B, S, D)),
            "k": _w((lambda *s: torch.randn(*s, dtype=torch.bfloat16) * 0.4)(B, S, D)),
            "v": _w((lambda *s: torch.randn(*s, dtype=torch.bfloat16) * 0.4)(B, S, D)),
            "shift_k": _w((lambda *s: torch.randn(*s, dtype=torch.bfloat16) * 0.4)(D, ks) * 0.5),
            "ssm_k": _w((lambda *s: torch.randn(*s, dtype=torch.bfloat16) * 0.4)(D, S) * (1.0 / S ** 0.5)),
            "ssm_D": _w((lambda *s: torch.randn(*s, dtype=torch.bfloat16) * 0.4)(D)),
        }
    _A_in = _A_setup()

    def _B_setup():
        B, L, D, N = 1, 2048, 448, 256
        A_re = -(lambda _x: torch.exp(torch.as_tensor(_x)))((lambda *s: torch.randn(*s, dtype=torch.bfloat16) * 6.4)(D, N))
        A_im = torch.pi * (lambda *s: torch.randn(*s, dtype=torch.bfloat16) * 0.05)(D, N)
        B_re = (lambda *s: torch.randn(*s, dtype=torch.bfloat16) * 0.1)(D, N)
        B_im = (lambda *s: torch.randn(*s, dtype=torch.bfloat16) * 0.1)(D, N)
        C_re = (lambda *s: torch.randn(*s, dtype=torch.bfloat16) * 0.1)(D, N)
        C_im = (lambda *s: torch.randn(*s, dtype=torch.bfloat16) * 0.1)(D, N)
        log_dt = (lambda *s: torch.randn(*s, dtype=torch.bfloat16) * 0.05)(D) * 0.5 - 4.0
        Dskip = (lambda *s: torch.randn(*s, dtype=torch.bfloat16) * 0.05)(D)
        return {
            "u": _w((lambda *s: torch.randn(*s, dtype=torch.bfloat16) * 0.05)(B, L, D)),
            "A_re": _w(A_re),
            "A_im": _w(A_im),
            "B_re": _w(B_re),
            "B_im": _w(B_im),
            "C_re": _w(C_re),
            "C_im": _w(C_im),
            "log_dt": _w(log_dt),
            "Dskip": _w(Dskip),
        }
    _B_in = _B_setup()

    return {
        "A_q": _A_in["q"],
        "A_k": _A_in["k"],
        "A_v": _A_in["v"],
        "A_shift_k": _A_in["shift_k"],
        "A_ssm_k": _A_in["ssm_k"],
        "A_ssm_D": _A_in["ssm_D"],
        "B_u": _B_in["u"],
        "B_A_re": _B_in["A_re"],
        "B_A_im": _B_in["A_im"],
        "B_B_re": _B_in["B_re"],
        "B_B_im": _B_in["B_im"],
        "B_C_re": _B_in["C_re"],
        "B_C_im": _B_in["C_im"],
        "B_log_dt": _B_in["log_dt"],
        "B_Dskip": _B_in["Dskip"],
    }

def reference(A_q, A_k, A_v, A_shift_k, A_ssm_k, A_ssm_D, B_u, B_A_re, B_A_im, B_B_re, B_B_im, B_C_re, B_C_im, B_log_dt, B_Dskip):
    def _A_ref(q, k, v, shift_k, ssm_k, ssm_D):
        B, S, D = q.shape
        ks = shift_k.shape[-1]
        k_pad = _pad(k, ((0, 0), (ks - 1, 0), (0, 0)))
        k_shift = torch.zeros_like(k)
        for t in range(ks):
            k_shift = k_shift + k_pad[:, t:t + S, :] * shift_k[:, ks - 1 - t][None, None, :]
        kv = k_shift * v
        L = 2 * S
        kv_pad = _pad(kv, ((0, 0), (0, S), (0, 0)))
        kf_pad = _pad(ssm_k, ((0, 0), (0, S)))
        kv_f = (lambda x, axes=(-2,-1): torch.fft.rfft2(x.float(), dim=axes))(kv_pad[:, None, :, :], axes=(1, 2))
        kf_f = (lambda x, axes=(-2,-1): torch.fft.rfft2(x.float(), dim=axes))(kf_pad[:, None, :], axes=(1, 2))
        kf_f = (lambda x, *d: x.permute(*d))(kf_f, 1, 2, 0)
        y_f = kv_f * kf_f[None, :, :, :]
        y = (lambda x, s, axes=(-2,-1): torch.fft.irfft2(x, s=s, dim=axes).to(torch.bfloat16))(y_f, (1, L), axes=(1, 2))[:, 0, :S, :]
        y = y + kv * ssm_D[None, None, :]
        return q * y

    def _B_ref(u, A_re, A_im, B_re, B_im, C_re, C_im, log_dt, Dskip):
        Bsz, L, D = u.shape
        dt = torch.exp(log_dt)[:, None]
        A = A_re + 1j * A_im
        Bc = B_re + 1j * B_im
        Cc = C_re + 1j * C_im
        logdA = dt * A
        dB = dt * Bc
        l = (lambda x, dt: x.to(dt))(torch.arange(L), A_re.dtype)
        P = torch.exp(logdA[:, :, None] * l[None, None, :])
        K = torch.einsum("dn,dnl,dn->dl", Cc, P, dB).real
        L2 = 2 * L
        Kp = _pad(K, ((0, 0), (0, L)))
        up = (lambda x, *d: x.permute(*d))(u, 0, 2, 1)
        up = _pad(up, ((0, 0), (0, 0), (0, L)))
        Kf = (lambda x, axes=(-2,-1): torch.fft.rfft2(x.float(), dim=axes))(Kp[:, None, :], axes=(-2, -1))
        Uf = (lambda x, axes=(-2,-1): torch.fft.rfft2(x.float(), dim=axes))(up[:, :, None, :], axes=(-2, -1))
        Yf = Uf * Kf[None, :, :, :]
        y = (lambda x, s, axes=(-2,-1): torch.fft.irfft2(x, s=s, dim=axes).to(torch.bfloat16))(Yf, (1, L2), axes=(-2, -1))[:, :, 0, :L]
        y = (lambda x, *d: x.permute(*d))(y, 0, 2, 1) + u * Dskip[None, None, :]
        return y

    a = _A_ref(A_q, A_k, A_v, A_shift_k, A_ssm_k, A_ssm_D)
    b = _B_ref(B_u, B_A_re, B_A_im, B_B_re, B_B_im, B_C_re, B_C_im, B_log_dt, B_Dskip)
    return torch.concatenate([a, b], axis=-1)
```

```cpp
#include <cuda_runtime.h>
#include <cuda_bf16.h>
#include <cuda.h>
#include <stdint.h>

namespace {

constexpr int XS = 4368;
constexpr int KS = 8320;
constexpr int PS = 4224;
constexpr int WGR = 4 * PS + 2 * KS;
constexpr int RAWB = 16640;
constexpr int O_YB = 0;
constexpr int O_YA = 16768;
constexpr int O_RV = 33536;
constexpr int O_RQ = 50176;
constexpr int O_XB = 66816;
constexpr int O_XA = O_XB + 4 * XS;
constexpr int O_KB = O_XA + 4 * XS;
constexpr int O_WG = O_KB + 4 * KS;
constexpr int O_BAR = O_WG + 2 * WGR;
constexpr int SMEM_BYTES = O_BAR + 128;
enum { B_U = 0, B_KV = 8, B_Q = 16, B_S = 24, B_XB = 32, B_XA = 40, B_YB = 48, B_YA = 56 };
constexpr int TBL = 7680;

struct Params {
    CUtensorMap mu, mk, mv, mq;
    const __nv_bfloat16 *shift_k, *ssm_k, *ssm_D, *a_re, *a_im, *b_re, *b_im, *c_re, *c_im, *log_dt, *dskip;
    __nv_bfloat16* out;
};

#define STAMP(role, i)
#define GSTAMP(i)

__device__ __forceinline__ uint32_t lds32(uint32_t a) { uint32_t v; asm volatile("ld.shared.u32 %0, [%1];" : "=r"(v) : "r"(a)); return v; }
__device__ __forceinline__ uint32_t lds16(uint32_t a) { uint16_t v; asm volatile("ld.shared.u16 %0, [%1];" : "=h"(v) : "r"(a)); return v; }
__device__ __forceinline__ uint2 lds64(uint32_t a) { uint2 v; asm volatile("ld.shared.v2.u32 {%0,%1}, [%2];" : "=r"(v.x), "=r"(v.y) : "r"(a)); return v; }
__device__ __forceinline__ uint4 lds128(uint32_t a) { uint4 v; asm volatile("ld.shared.v4.u32 {%0,%1,%2,%3}, [%4];" : "=r"(v.x), "=r"(v.y), "=r"(v.z), "=r"(v.w) : "r"(a)); return v; }
__device__ __forceinline__ void sts16(uint32_t a, uint32_t v) { asm volatile("st.shared.u16 [%0], %1;" ::"r"(a), "h"((uint16_t)v) : "memory"); }
__device__ __forceinline__ void sts32(uint32_t a, uint32_t v) { asm volatile("st.shared.u32 [%0], %1;" ::"r"(a), "r"(v) : "memory"); }
__device__ __forceinline__ void sts64(uint32_t a, uint32_t x, uint32_t y) { asm volatile("st.shared.v2.u32 [%0], {%1,%2};" ::"r"(a), "r"(x), "r"(y) : "memory"); }
__device__ __forceinline__ void sts128(uint32_t a, uint32_t x, uint32_t y, uint32_t z, uint32_t w) { asm volatile("st.shared.v4.u32 [%0], {%1,%2,%3,%4};" ::"r"(a), "r"(x), "r"(y), "r"(z), "r"(w) : "memory"); }
__device__ __forceinline__ uint32_t ldg16(const void* p) { uint16_t v; asm volatile("ld.global.nc.u16 %0, [%1];" : "=h"(v) : "l"(p)); return v; }
__device__ __forceinline__ uint2 ldg64(const void* p) { uint2 v; asm volatile("ld.global.nc.v2.u32 {%0,%1}, [%2];" : "=r"(v.x), "=r"(v.y) : "l"(p)); return v; }
__device__ __forceinline__ uint32_t pack(float lo, float hi) { uint32_t r; asm("cvt.rn.bf16x2.f32 %0, %1, %2;" : "=r"(r) : "f"(hi), "f"(lo)); return r; }
__device__ __forceinline__ uint32_t hadd(uint32_t a, uint32_t b) { uint32_t r; asm("add.rn.bf16x2 %0, %1, %2;" : "=r"(r) : "r"(a), "r"(b)); return r; }
__device__ __forceinline__ uint32_t hmul(uint32_t a, uint32_t b) { uint32_t r; asm("mul.rn.bf16x2 %0, %1, %2;" : "=r"(r) : "r"(a), "r"(b)); return r; }
__device__ __forceinline__ uint32_t hfma(uint32_t a, uint32_t b, uint32_t c) { uint32_t r; asm("fma.rn.bf16x2 %0, %1, %2, %3;" : "=r"(r) : "r"(a), "r"(b), "r"(c)); return r; }
__device__ __forceinline__ uint32_t hneg(uint32_t a) { uint32_t r; asm("neg.bf16x2 %0, %1;" : "=r"(r) : "r"(a)); return r; }
__device__ __forceinline__ uint32_t prmt(uint32_t a, uint32_t b, uint32_t s) { uint32_t r; asm("prmt.b32 %0, %1, %2, %3;" : "=r"(r) : "r"(a), "r"(b), "r"(s)); return r; }
__device__ __forceinline__ float blo(uint32_t v) { return __uint_as_float(v << 16); }
__device__ __forceinline__ float bhi(uint32_t v) { return __uint_as_float(v & 0xffff0000u); }
__device__ __forceinline__ uint32_t mapa(uint32_t a, uint32_t r) { uint32_t o; asm("mapa.shared::cluster.u32 %0, %1, %2;" : "=r"(o) : "r"(a), "r"(r)); return o; }
__device__ __forceinline__ void st_async(uint32_t a, uint32_t x, uint32_t y, uint32_t z, uint32_t w, uint32_t bar) {
    asm volatile("st.async.weak.shared::cluster.mbarrier::complete_tx::bytes.v4.b32 [%0], {%1,%2,%3,%4}, [%5];" ::"r"(a), "r"(x), "r"(y), "r"(z), "r"(w), "r"(bar) : "memory");
}
__device__ __forceinline__ void wait_bar(uint32_t bar) {
    uint32_t done = 0;
    for (int it = 0; it < (1 << 22); it++) {
        asm volatile("{ .reg .pred p; mbarrier.try_wait.parity.acquire.cluster.shared::cta.b64 p, [%1], 0; selp.u32 %0, 1, 0, p; }" : "=r"(done) : "r"(bar) : "memory");
        if (done) break;
    }
}
__device__ __forceinline__ void bar_sync(int id, int n) { asm volatile("bar.sync %0, %1;" ::"r"(id), "r"(n) : "memory"); }
__device__ __forceinline__ void bar_arrive(int id, int n) { asm volatile("bar.arrive %0, %1;" ::"r"(id), "r"(n) : "memory"); }
__device__ __forceinline__ void tma3d(uint32_t dst, const CUtensorMap* m, int c0, int c1, uint32_t bar) {
    asm volatile("cp.async.bulk.tensor.3d.shared::cluster.global.mbarrier::complete_tx::bytes [%0], [%1, {%3, %4, %5}], [%2];" ::"r"(dst), "l"(m), "r"(bar), "r"(c0), "r"(c1), "r"(0) : "memory");
}

template <int OFF, int SC>
__device__ __forceinline__ void wgmma32(float (&d)[128], uint32_t a0, uint32_t a1, uint32_t a2, uint32_t a3, uint32_t dlo) {
    asm volatile("{ .reg .b64 dsc; mov.b64 dsc, {%20, 8};\n wgmma.mma_async.sync.aligned.m64n32k16.f32.bf16.bf16 {%0, %1, %2, %3, %4, %5, %6, %7, %8, %9, %10, %11, %12, %13, %14, %15}, {%16, %17, %18, %19}, dsc, %21, 1, 1, 0; }"
                 : "+f"(d[OFF + 0]), "+f"(d[OFF + 1]), "+f"(d[OFF + 2]), "+f"(d[OFF + 3]), "+f"(d[OFF + 4]), "+f"(d[OFF + 5]), "+f"(d[OFF + 6]), "+f"(d[OFF + 7]), "+f"(d[OFF + 8]), "+f"(d[OFF + 9]), "+f"(d[OFF + 10]), "+f"(d[OFF + 11]), "+f"(d[OFF + 12]), "+f"(d[OFF + 13]), "+f"(d[OFF + 14]), "+f"(d[OFF + 15])
                 : "r"(a0), "r"(a1), "r"(a2), "r"(a3), "r"(dlo), "n"(SC));
}
#define WG_FENCE asm volatile("wgmma.fence.sync.aligned;" ::: "memory");
#define WG_COMMIT asm volatile("wgmma.commit_group.sync.aligned;" ::: "memory");
#define WG_WAIT(n) asm volatile("wgmma.wait_group.sync.aligned %0;" ::"n"(n) : "memory");

template <int J, int B, int NB>
__device__ __forceinline__ void step_ranges(float (&d)[128], uint32_t (&a)[64], uint32_t desc) {
    if constexpr (B < NB) {
        wgmma32<16 * B, J != 0>(d, a[4 * J], a[4 * J + 1], a[4 * J + 2], a[4 * J + 3], desc + (32 * B + 16 * J));
        step_ranges<J, B + 1, NB>(d, a, desc);
    }
}
template <int P>
__device__ __forceinline__ void group(float (&d)[128], uint32_t (&a)[64], uint32_t desc) {
    WG_FENCE
    step_ranges<2 * P, 0, 8 - P>(d, a, desc);
    step_ranges<2 * P + 1, 0, 8 - P>(d, a, desc);
    WG_COMMIT
}
template <int B>
__device__ __forceinline__ void epi(float (&d)[128], uint32_t& carry, uint32_t pw) {
    uint32_t r[4];
#pragma unroll
    for (int k = 3; k >= 0; k--) {
        const int i = 4 * B + k;
        r[k] = pack(d[4 * i], d[4 * i + 1]);
        if (i < 31) r[k] = hadd(r[k], carry);
        if (i > 0) carry = pack(d[4 * i + 2], d[4 * i + 3]);
    }
    asm volatile("stmatrix.sync.aligned.m8n8.x4.trans.shared.b16 [%0], {%1,%2,%3,%4};" ::"r"(pw - B * 512), "r"(r[0]), "r"(r[1]), "r"(r[2]), "r"(r[3]) : "memory");
}
template <int P>
__device__ __forceinline__ void loadA(uint32_t (&a)[64], uint32_t ax) {
#pragma unroll
    for (int j = 2 * P; j < 2 * P + 2; j++) {
        a[4 * j] = lds32(ax + 256 * j);
        a[4 * j + 1] = lds32(ax + 256 * j + 128);
        a[4 * j + 2] = lds32(ax + 256 * j + 16);
        a[4 * j + 3] = lds32(ax + 256 * j + 144);
    }
}
__device__ __forceinline__ void reduce_push(uint32_t pr, uint32_t dst0, uint32_t dst1, uint32_t bar0, uint32_t bar1) {
#pragma unroll
    for (int h = 0; h < 2; h++) {
        uint4 p0 = lds128(pr + h * 2048), p1 = lds128(pr + h * 2048 + PS), p2 = lds128(pr + h * 2048 + 2 * PS), p3 = lds128(pr + h * 2048 + 3 * PS);
        st_async(h ? dst1 : dst0, hadd(hadd(p0.x, p1.x), hadd(p2.x, p3.x)), hadd(hadd(p0.y, p1.y), hadd(p2.y, p3.y)),
                 hadd(hadd(p0.z, p1.z), hadd(p2.z, p3.z)), hadd(hadd(p0.w, p1.w), hadd(p2.w, p3.w)), h ? bar1 : bar0);
    }
}

struct C2 { uint32_t re, im; };
__device__ __forceinline__ C2 cmul(C2 a, C2 b) { C2 r; r.re = hfma(a.re, b.re, hneg(hmul(a.im, b.im))); r.im = hfma(a.re, b.im, hmul(a.im, b.re)); return r; }
__device__ __forceinline__ C2 cmulc(C2 a, C2 b) { C2 r; r.re = hfma(a.re, b.re, hmul(a.im, b.im)); r.im = hfma(a.im, b.re, hneg(hmul(a.re, b.im))); return r; }
__device__ __forceinline__ void csq(float& re, float& im) { float t = re * im; re = fmaf(re, re, -im * im); im = t + t; }
__device__ __forceinline__ float ex2(float x) { float r; asm("ex2.approx.ftz.f32 %0, %1;" : "=f"(r) : "f"(x)); return r; }
__device__ __forceinline__ void mma16816(float (&c)[4], uint32_t a0, uint32_t a1, uint32_t a2, uint32_t a3, uint32_t b0, uint32_t b1) {
    asm volatile("mma.sync.aligned.m16n8k16.row.col.f32.bf16.bf16.f32 {%0,%1,%2,%3}, {%4,%5,%6,%7}, {%8,%9}, {%0,%1,%2,%3};"
                 : "+f"(c[0]), "+f"(c[1]), "+f"(c[2]), "+f"(c[3]) : "r"(a0), "r"(a1), "r"(a2), "r"(a3), "r"(b0), "r"(b1));
}
__device__ __forceinline__ void kgen_tables(const uint32_t (&p)[6], float dt, uint32_t tb, int lane) {
    float gr[2][11], gi[2][11], wr[2], wi[2];
#pragma unroll
    for (int m = 0; m < 2; m++) {
        float a = (m ? bhi(p[0]) : blo(p[0])) * dt, om = (m ? bhi(p[1]) : blo(p[1])) * dt;
        float br = (m ? bhi(p[2]) : blo(p[2])) * dt, bi = (m ? bhi(p[3]) : blo(p[3])) * dt;
        float cr = m ? bhi(p[4]) : blo(p[4]), ci = m ? bhi(p[5]) : blo(p[5]);
        wr[m] = fmaf(cr, br, -ci * bi);
        wi[m] = -fmaf(cr, bi, ci * br);
        float al = a * 1.4426950408889634f;
        float r1 = ex2(al), r64 = ex2(al * 64.f);
        float re = r1 * __cosf(om), im = r1 * __sinf(om);
        gr[m][0] = re; gi[m][0] = im;
#pragma unroll
        for (int s = 1; s < 6; s++) { csq(re, im); gr[m][s] = re; gi[m][s] = im; }
        re = r64 * __cosf(om * 64.f); im = r64 * __sinf(om * 64.f);
        gr[m][6] = re; gi[m][6] = im;
#pragma unroll
        for (int s = 7; s < 11; s++) { csq(re, im); gr[m][s] = re; gi[m][s] = im; }
    }
    C2 z[11];
#pragma unroll
    for (int s = 0; s < 11; s++) { z[s].re = pack(gr[0][s], gr[1][s]); z[s].im = pack(gi[0][s], gi[1][s]); }
    C2 P[8], Q[8], T[8];
    P[0].re = 0x3f803f80u; P[0].im = 0;
    P[1] = z[3]; P[2] = z[4]; P[3] = cmul(z[3], z[4]); P[4] = z[5]; P[5] = cmul(z[5], z[3]); P[6] = cmul(z[5], z[4]); P[7] = cmul(z[5], P[3]);
    Q[0].re = pack(wr[0], wr[1]); Q[0].im = pack(wi[0], wi[1]);
    Q[1] = cmulc(Q[0], z[0]); Q[2] = cmulc(Q[0], z[1]); Q[3] = cmulc(Q[1], z[1]); Q[4] = cmulc(Q[0], z[2]);
    Q[5] = cmulc(Q[1], z[2]); Q[6] = cmulc(Q[2], z[2]); Q[7] = cmulc(Q[3], z[2]);
#pragma unroll
    for (int g = 0; g < 8; g++) sts128(tb + g * 576 + lane * 16, P[g].re, P[g].im, Q[g].re, Q[g].im);
    T[0] = cmulc(Q[0], z[8]); T[1] = cmulc(Q[2], z[8]); T[2] = cmulc(Q[4], z[8]); T[3] = cmulc(Q[6], z[8]);
    T[4] = cmulc(Q[0], z[9]); T[5] = cmulc(Q[4], z[9]); T[6] = cmulc(T[0], z[10]); T[7] = cmulc(T[4], z[10]);
#pragma unroll
    for (int g = 0; g < 8; g++) sts64(tb + 4608 + g * 288 + lane * 8, T[g].re, T[g].im);
    sts128(tb + 6912 + lane * 16, z[6].re, z[6].im, z[7].re, z[7].im);
    sts64(tb + 7424 + lane * 8, z[9].re, z[9].im);
}
__device__ __forceinline__ void kgen_mma(float (&acc)[6][4], uint32_t tb, int g, int t) {
    const uint32_t apq = tb + g * 576 + t * 16, at = tb + 4608 + g * 288 + t * 8, am1 = tb + 6912 + t * 16, am2 = tb + 7424 + t * 8;
#pragma unroll 2
    for (int s = 0; s < 8; s++) {
        uint4 pq = lds128(apq + s * 64), m1 = lds128(am1 + s * 64);
        uint2 tt = lds64(at + s * 32), m2 = lds64(am2 + s * 32);
        C2 P0 = {pq.x, pq.y}, z64 = {m1.x, m1.y}, z128 = {m1.z, m1.w}, T = {tt.x, tt.y}, z512 = {m2.x, m2.y};
        C2 P1 = cmul(P0, z64), P2 = cmul(P0, z128), P3 = cmul(P1, z128), T2 = cmulc(T, z512);
        mma16816(acc[0], P0.re, P1.re, P0.im, P1.im, pq.z, pq.w);
        mma16816(acc[1], P0.re, P1.re, P0.im, P1.im, T.re, T.im);
        mma16816(acc[2], P0.re, P1.re, P0.im, P1.im, T2.re, T2.im);
        mma16816(acc[3], P2.re, P3.re, P2.im, P3.im, pq.z, pq.w);
        mma16816(acc[4], P2.re, P3.re, P2.im, P3.im, T.re, T.im);
        mma16816(acc[5], P2.re, P3.re, P2.im, P3.im, T2.re, T2.im);
    }
}

template <bool GATE>
__device__ __forceinline__ void final_pass(uint32_t ybase, uint32_t qbase, __nv_bfloat16* outp, int w, int nw, int lane) {
    const int r = lane & 7, k = lane >> 3, g = lane >> 2, t = lane & 3;
    const int ch = 8 * ((r >> 1) & 1) + 2 * k + (r & 1);
    const uint32_t ya = ybase + ch * 1040 + (ch >> 3) * 64 + (r >> 2) * 32;
    const uint32_t qa = qbase + g * 2080 + (2 * (t >> 1) + 1) * 32 + (t & 1) * 16;
    char* op = (char*)outp + (size_t)(16 * (t >> 1) + g) * 1792 + (t & 1) * 16;
#pragma unroll 2
    for (int i = w; i < 32; i += nw) {
        const int c = (i & 1) + 4 * (i >> 1);
        uint32_t v0, v1, v2, v3;
        asm volatile("ldmatrix.sync.aligned.m8n8.x4.trans.shared.b16 {%0,%1,%2,%3}, [%4];" : "=r"(v0), "=r"(v1), "=r"(v2), "=r"(v3) : "r"(ya + c * 16));
        if (GATE) {
            uint4 q = lds128(qa + c * 32);
            v0 = hmul(v0, q.x); v1 = hmul(v1, q.y); v2 = hmul(v2, q.z); v3 = hmul(v3, q.w);
        }
        asm volatile("st.global.v4.b32 [%0], {%1,%2,%3,%4};" ::"l"(op + (size_t)c * (8 * 1792)), "r"(v0), "r"(v1), "r"(v2), "r"(v3) : "memory");
    }
}

__global__ void __cluster_dims__(4, 1, 1) __launch_bounds__(384, 1) fused_kernel(const __grid_constant__ Params prm) {
    extern __shared__ __align__(1024) char smem[];
    const uint32_t base = (uint32_t)__cvta_generic_to_shared(smem);
    const uint32_t bars = base + O_BAR;
    const int wg = __shfl_sync(0xffffffff, threadIdx.x >> 7, 0);
    const int tid = threadIdx.x & 127, lane = threadIdx.x & 31;
    const int w = __shfl_sync(0xffffffff, tid >> 5, 0);
    const int rank = blockIdx.x & 3, cl = blockIdx.x >> 2;
    const int ch0 = 16 * cl + 4 * rank;
    if (wg == 2) {
        GSTAMP(14);
        asm volatile("setmaxnreg.dec.sync.aligned.u32 56;");
        if (tid == 0) {
#pragma unroll
            for (int i = 0; i < 8; i++) asm volatile("mbarrier.init.shared.b64 [%0], 1;" ::"r"(bars + 8 * i) : "memory");
            asm volatile("fence.mbarrier_init.release.cluster;" ::: "memory");
            asm volatile("fence.proxy.async.shared::cta;" ::: "memory");
            asm volatile("mbarrier.arrive.expect_tx.shared.b64 _, [%0], %1;" ::"r"(bars + B_U), "r"(RAWB) : "memory");
            tma3d(base + O_YB, &prm.mu, 16 * cl, 64 * rank - 1, bars + B_U);
            asm volatile("mbarrier.arrive.expect_tx.shared.b64 _, [%0], %1;" ::"r"(bars + B_KV), "r"(2 * RAWB) : "memory");
            asm volatile("mbarrier.arrive.expect_tx.shared.b64 _, [%0], %1;" ::"r"(bars + B_Q), "r"(RAWB) : "memory");
            asm volatile("mbarrier.arrive.expect_tx.shared.b64 _, [%0], %1;" ::"r"(bars + B_S), "r"(16384) : "memory");
#pragma unroll
            for (int i = 4; i < 8; i++) asm volatile("mbarrier.arrive.expect_tx.shared.b64 _, [%0], %1;" ::"r"(bars + 8 * i), "r"(16384) : "memory");
        }
        __syncwarp();
        asm volatile("barrier.cluster.arrive.relaxed.aligned;" ::: "memory");
        if (tid == 0) {
            tma3d(base + O_YA, &prm.mk, 16 * cl, 64 * rank - 1, bars + B_KV);
            tma3d(base + O_RV, &prm.mv, 16 * cl, 64 * rank - 1, bars + B_KV);
            asm volatile("cp.async.bulk.prefetch.L2.global [%0], %1;" ::"l"(prm.ssm_k + (size_t)ch0 * 2048), "r"(16384) : "memory");
            tma3d(base + O_RQ, &prm.mq, 16 * cl, 64 * rank - 1, bars + B_Q);
        }
        __syncwarp();
        const int c4 = tid & 3, gam = tid >> 2;
        uint32_t W[4][2];
        {
            const uint4* sp = (const uint4*)(prm.shift_k + (16 * cl + 4 * c4) * 4);
            uint4 s0 = __ldg(sp), s1 = __ldg(sp + 1);
            W[0][0] = prmt(s0.x, s0.z, 0x5410); W[1][0] = prmt(s0.x, s0.z, 0x7632); W[2][0] = prmt(s0.y, s0.w, 0x5410); W[3][0] = prmt(s0.y, s0.w, 0x7632);
            W[0][1] = prmt(s1.x, s1.z, 0x5410); W[1][1] = prmt(s1.x, s1.z, 0x7632); W[2][1] = prmt(s1.y, s1.w, 0x5410); W[3][1] = prmt(s1.y, s1.w, 0x7632);
        }
        const float dA = __bfloat162float(prm.ssm_D[ch0 + w]);
        asm volatile("barrier.cluster.wait.acquire.aligned;" ::: "memory");
        STAMP(2, 0);
        const uint32_t roff = (gam + 1) * 32 + c4 * 8;
        const uint32_t xdst = mapa(base + 16 * (255 - 64 * rank - gam), c4);
        wait_bar(bars + B_U);
        STAMP(2, 1);
        {
            const uint32_t bx = mapa(bars + B_XB, c4);
#pragma unroll
            for (int pass = 0; pass < 2; pass++) {
                uint2 R[8];
#pragma unroll
                for (int i = 0; i < 8; i++) R[i] = lds64(base + O_YB + roff + pass * 1024 + i * 2080);
                const uint32_t dd = xdst + O_XB - pass * 512;
                st_async(dd, prmt(R[7].x, R[6].x, 0x5410), prmt(R[5].x, R[4].x, 0x5410), prmt(R[3].x, R[2].x, 0x5410), prmt(R[1].x, R[0].x, 0x5410), bx);
                st_async(dd + 2 * XS, prmt(R[7].y, R[6].y, 0x5410), prmt(R[5].y, R[4].y, 0x5410), prmt(R[3].y, R[2].y, 0x5410), prmt(R[1].y, R[0].y, 0x5410), bx);
                st_async(dd + XS, prmt(R[7].x, R[6].x, 0x7632), prmt(R[5].x, R[4].x, 0x7632), prmt(R[3].x, R[2].x, 0x7632), prmt(R[1].x, R[0].x, 0x7632), bx);
                st_async(dd + 3 * XS, prmt(R[7].y, R[6].y, 0x7632), prmt(R[5].y, R[4].y, 0x7632), prmt(R[3].y, R[2].y, 0x7632), prmt(R[1].y, R[0].y, 0x7632), bx);
            }
        }
        STAMP(2, 2);
        bar_sync(3, 384);
        const uint32_t ka = base + O_WG + (w >> 1) * WGR + 4 * PS + (w & 1) * KS;
        if (lane == 0) {
            asm volatile("fence.proxy.async.shared::cta;" ::: "memory");
            asm volatile("cp.async.bulk.shared::cluster.global.mbarrier::complete_tx::bytes [%0], [%1], %2, [%3];" ::"r"(ka + 16), "l"(prm.ssm_k + (size_t)(ch0 + w) * 2048), "r"(4096), "r"(bars + B_S) : "memory");
            sts128(ka, 0, 0, 0, 0);
            sts128(ka + 4160, 0, 0, 0, 0);
        }
        __syncwarp();
        STAMP(2, 3);
        wait_bar(bars + B_KV);
        STAMP(2, 4);
        {
            const uint32_t bx = mapa(bars + B_XA, c4);
#pragma unroll 1
            for (int pass = 0; pass < 2; pass++) {
                const uint32_t kb = base + O_YA + roff + pass * 1024, vb = base + O_RV + roff + pass * 1024;
                uint2 k3 = lds64(kb - 32 + 5 * 2080), k2 = lds64(kb - 32 + 6 * 2080), k1 = lds64(kb - 32 + 7 * 2080);
                uint2 R[8];
#pragma unroll
                for (int i = 0; i < 8; i++) {
                    uint2 k0 = lds64(kb + i * 2080), v = lds64(vb + i * 2080);
                    R[i].x = hmul(hfma(k0.x, W[0][0], hfma(k1.x, W[1][0], hfma(k2.x, W[2][0], hmul(k3.x, W[3][0])))), v.x);
                    R[i].y = hmul(hfma(k0.y, W[0][1], hfma(k1.y, W[1][1], hfma(k2.y, W[2][1], hmul(k3.y, W[3][1])))), v.y);
                    k3 = k2; k2 = k1; k1 = k0;
                }
                const uint32_t dd = xdst + O_XA - pass * 512;
                st_async(dd, prmt(R[7].x, R[6].x, 0x5410), prmt(R[5].x, R[4].x, 0x5410), prmt(R[3].x, R[2].x, 0x5410), prmt(R[1].x, R[0].x, 0x5410), bx);
                st_async(dd + 2 * XS, prmt(R[7].y, R[6].y, 0x5410), prmt(R[5].y, R[4].y, 0x5410), prmt(R[3].y, R[2].y, 0x5410), prmt(R[1].y, R[0].y, 0x5410), bx);
                st_async(dd + XS, prmt(R[7].x, R[6].x, 0x7632), prmt(R[5].x, R[4].x, 0x7632), prmt(R[3].x, R[2].x, 0x7632), prmt(R[1].x, R[0].x, 0x7632), bx);
                st_async(dd + 3 * XS, prmt(R[7].y, R[6].y, 0x7632), prmt(R[5].y, R[4].y, 0x7632), prmt(R[3].y, R[2].y, 0x7632), prmt(R[1].y, R[0].y, 0x7632), bx);
            }
        }
        STAMP(2, 5);
        wait_bar(bars + B_S);
#pragma unroll 2
        for (int i = 0; i < 8; i++) {
            const uint32_t a = ka + 16 + (i * 32 + lane) * 16;
            uint4 e = lds128(a);
            uint32_t p = lds32(a - 4);
            if (i == 0 && lane == 0) {
                e.x = (e.x & 0xffff0000u) | (pack(blo(e.x) + dA, 0.f) & 0xffffu);
                sts32(a, e.x);
            }
            sts128(a + 4160, prmt(p, e.x, 0x5432), prmt(e.x, e.y, 0x5432), prmt(e.y, e.z, 0x5432), prmt(e.z, e.w, 0x5432));
        }
        bar_arrive(4, 256);
        bar_arrive(5, 256);
        STAMP(2, 6);
        __nv_bfloat16* ob = prm.out + (size_t)(512 * rank) * 896 + 16 * cl;
        wait_bar(bars + B_YB);
        STAMP(2, 7);
        final_pass<false>(base + O_YB, 0, ob + 448, w, 4, lane);
        STAMP(2, 8);
        wait_bar(bars + B_Q);
        wait_bar(bars + B_YA);
        STAMP(2, 9);
        final_pass<true>(base + O_YA, base + O_RQ, ob, w, 4, lane);
        STAMP(2, 10);
        GSTAMP(15);
    } else {
        const int g = lane >> 2, t = lane & 3;
        const uint32_t wgb = base + O_WG + wg * WGR;
        {
            const int chl = 2 * wg + (w >> 1);
            const size_t po = (size_t)(ch0 + chl) * 256 + (w & 1) * 128 + lane * 4;
            uint2 pv[6];
            const uint32_t ldt16 = ldg16(prm.log_dt + ch0 + chl);
            pv[0] = ldg64(prm.a_re + po); pv[1] = ldg64(prm.a_im + po);
            pv[2] = ldg64(prm.b_re + po); pv[3] = ldg64(prm.b_im + po);
            pv[4] = ldg64(prm.c_re + po); pv[5] = ldg64(prm.c_im + po);
            const uint32_t dsk16 = ldg16(prm.dskip + ch0 + chl);
            asm volatile("setmaxnreg.inc.sync.aligned.u32 224;");
            asm volatile("barrier.cluster.arrive.relaxed.aligned;" ::: "memory");
            {
                if (lane < 17) sts128(base + O_XB + ((w >> 1) * 4 + 2 * wg + (w & 1)) * XS + 4096 + lane * 16, 0, 0, 0, 0);
                else if (lane == 17) sts128(base + O_KB + chl * KS + (w & 1) * 4160, 0, 0, 0, 0);
            }
            const float dt = __bfloat162float(__float2bfloat16_rn(expf(blo(ldt16))));
            const float dsk = blo(dsk16);
            const uint32_t tb = wgb + w * TBL;
            float acc[6][4];
#pragma unroll
            for (int i = 0; i < 6; i++) { acc[i][0] = 0.f; acc[i][1] = 0.f; acc[i][2] = 0.f; acc[i][3] = 0.f; }
            STAMP(wg, 0);
#pragma unroll 1
            for (int b = 0; b < 2; b++) {
                uint32_t p[6];
#pragma unroll
                for (int i = 0; i < 6; i++) p[i] = b ? pv[i].y : pv[i].x;
                __syncwarp();
                kgen_tables(p, dt, tb, lane);
                __syncwarp();
                kgen_mma(acc, tb, g, t);
                STAMP(wg, 1 + b);
            }
            __syncwarp();
            const int odd = w & 1;
#pragma unroll
            for (int n = 0; n < 3; n++) {
                float s0 = odd ? acc[n][0] : acc[3 + n][0], s1 = odd ? acc[n][1] : acc[3 + n][1], s2 = odd ? acc[n][2] : acc[3 + n][2], s3 = odd ? acc[n][3] : acc[3 + n][3];
                sts128(tb + n * 512 + lane * 16, __float_as_uint(s0), __float_as_uint(s1), __float_as_uint(s2), __float_as_uint(s3));
            }
            bar_sync(1 + wg, 128);
            const uint32_t zb = wgb + (w & 2) * TBL + 2048;
            {
                const uint32_t ob = wgb + (w ^ 1) * TBL + lane * 16;
                float f[3][4];
#pragma unroll
                for (int n = 0; n < 3; n++) {
                    uint4 o = lds128(ob + n * 512);
                    f[n][0] = (odd ? acc[3 + n][0] : acc[n][0]) + __uint_as_float(o.x);
                    f[n][1] = (odd ? acc[3 + n][1] : acc[n][1]) + __uint_as_float(o.y);
                    f[n][2] = (odd ? acc[3 + n][2] : acc[n][2]) + __uint_as_float(o.z);
                    f[n][3] = (odd ? acc[3 + n][3] : acc[n][3]) + __uint_as_float(o.w);
                }
                if (!odd && lane == 0) f[0][0] += dsk;
                const int bs10 = t < 2 ? 256 + 2 * t : (t == 2 ? 384 : 544), ml1 = t < 2 ? 4 : (t == 2 ? 2 : 1);
                const int bs11 = t < 3 ? bs10 + 1 : 576;
                const int bs20 = t < 2 ? 448 + t : (t == 2 ? 512 : 608), ml2 = t < 2 ? 2 : 1;
                const int bs21 = t == 3 ? 640 : 672;
#pragma unroll
                for (int h = 0; h < 2; h++) {
                    const int b = 16 * odd + 8 * h + g;
                    sts32(zb + 2 * (8 * b + 2 * t), pack(f[0][2 * h], f[0][2 * h + 1]));
                    const uint32_t v1 = pack(f[1][2 * h], f[1][2 * h + 1]), v2 = pack(f[2][2 * h], f[2][2 * h + 1]);
                    sts16(zb + 2 * (bs10 + ml1 * b), v1);
                    sts16(zb + 2 * (bs11 + ml1 * b), v1 >> 16);
                    sts16(zb + 2 * (bs20 + ml2 * b), v2);
                    sts16(zb + 2 * (bs21 + b), v2 >> 16);
                }
            }
            bar_sync(1 + wg, 128);
            {
                const uint32_t ke = base + O_KB + chl * KS + 16 + lane * 16 + odd * 512;
                if (!odd) {
                    uint4 e = lds128(zb + lane * 16);
                    uint32_t p = lane ? lds32(zb + lane * 16 - 4) : 0;
                    sts128(ke, e.x, e.y, e.z, e.w);
                    sts128(ke + 4160, prmt(p, e.x, 0x5432), prmt(e.x, e.y, 0x5432), prmt(e.y, e.z, 0x5432), prmt(e.z, e.w, 0x5432));
                } else {
                    uint2 v = lds64(zb + 512 + lane * 8);
                    uint32_t v4 = lds32(zb + 512 + lane * 8 + 8), pw_ = lds32(zb + 508 + lane * 8);
                    uint32_t d0 = prmt(v.x, 0, 0x1010), d2 = prmt(v.y, 0, 0x1010);
                    sts128(ke, d0, prmt(v.x, v.y, 0x5432), d2, prmt(v.y, v4, 0x5432));
                    sts128(ke + 4160, lane ? d0 : prmt(pw_, v.x, 0x5432), v.x, d2, v.y);
                }
                {
                    const uint32_t za = zb + 768 + (odd * 32 + lane) * 4;
                    uint32_t v = lds32(za), v2 = lds32(za + 4);
                    uint32_t d0 = prmt(v, 0, 0x1010), d1 = prmt(v, 0, 0x3232);
                    sts128(ke + 1024, d0, v, d1, prmt(v2, 0, 0x1010));
                    sts128(ke + 1024 + 4160, d0, d0, d1, prmt(v, v2, 0x5432));
                }
#pragma unroll
                for (int h = 0; h < 2; h++) {
                    const uint32_t za = zb + 1024 + (h * 64 + odd * 32 + lane) * 2;
                    uint32_t v0 = lds16(za), v1 = lds16(za + 2);
                    uint32_t d0 = v0 * 0x10001u, d1 = v1 * 0x10001u, m = v0 | (v1 << 16);
                    sts128(ke + 2048 + h * 1024, d0, d0, (lane & 1) ? d1 : m, d1);
                    sts128(ke + 2048 + h * 1024 + 4160, d0, d0, (lane & 1) ? m : d0, d1);
                }
            }
            asm volatile("fence.proxy.async.shared::cta;" ::: "memory");
            bar_sync(1 + wg, 128);
            if (lane < 2 * w) sts128(wgb + w * PS + lane * 16, 0, 0, 0, 0);
            bar_arrive(3, 384);
            asm volatile("barrier.cluster.wait.acquire.aligned;" ::: "memory");
            STAMP(wg, 3);
        }
        const uint32_t aoff = 16 + ((g & 1) ? 0 : 4160) + 4 * (8 * w + t + (g >> 1) - 3);
        const uint32_t pw = wgb + w * PS + 16 * (255 + 2 * w - lane);
        const uint32_t pr = wgb + tid * 16;
        const uint32_t yloc = base + ((4 * rank + 2 * wg) * 1040 + (rank >> 1) * 64) + (tid & 63) * 16;
        const uint32_t y0 = mapa(yloc, w >> 1), y1 = mapa(yloc, 2 + (w >> 1));
        const uint32_t yb0 = mapa(bars + B_YB, w >> 1), yb1 = mapa(bars + B_YB, 2 + (w >> 1));
        float d[128];
        uint32_t a[64];
        uint32_t carry = 0;
        {
            const uint32_t ax = base + O_KB + 2 * wg * KS + aoff;
            loadA<0>(a, ax); loadA<1>(a, ax); loadA<2>(a, ax); loadA<3>(a, ax); loadA<4>(a, ax); loadA<5>(a, ax); loadA<6>(a, ax); loadA<7>(a, ax);
        }
        wait_bar(bars + B_XB);
        asm volatile("fence.proxy.async.shared::cta;" ::: "memory");
        STAMP(wg, 4);
#pragma unroll 1
        for (int c = 0; c < 4; c++) {
            const uint32_t xa = base + O_XB + (c >> 1) * (4 * XS) + (2 * wg + (c & 1)) * XS;
            const uint32_t desc = ((xa & 0x3FFFF) >> 4) | 0x10000;
            const uint32_t axn = (c == 0 ? base + O_KB + (2 * wg + 1) * KS : wgb + 4 * PS + ((c + 1) & 1) * KS) + aoff;
            if (c == 2) {
                wait_bar(bars + B_XA);
                asm volatile("fence.proxy.async.shared::cta;" ::: "memory");
            }
            group<0>(d, a, desc);
            if (c > 0) {
                const uint32_t yo = ((c - 1) >> 1) * O_YA + ((c - 1) & 1) * 1040, bo = ((c - 1) >> 1) * 8;
                bar_sync(1 + wg, 128);
                reduce_push(pr, y0 + yo, y1 + yo, yb0 + bo, yb1 + bo);
            }
            group<1>(d, a, desc);
            bar_sync(1 + wg, 128);
            if (c == 1) bar_sync(4 + wg, 256);
#define STAGE(P) WG_WAIT(1) epi<7 - P>(d, carry, pw); loadA<P>(a, axn);
            STAGE(0) group<2>(d, a, desc);
            STAGE(1) group<3>(d, a, desc);
            STAGE(2) group<4>(d, a, desc);
            STAGE(3) group<5>(d, a, desc);
            STAGE(4) group<6>(d, a, desc);
            STAGE(5) group<7>(d, a, desc);
            STAGE(6)
            WG_WAIT(0) epi<0>(d, carry, pw); loadA<7>(a, axn);
            STAMP(wg, 5 + c);
        }
        bar_sync(1 + wg, 128);
        reduce_push(pr, y0 + O_YA + 1040, y1 + O_YA + 1040, yb0 + 8, yb1 + 8);
        STAMP(wg, 9);
    }
}

typedef CUresult (*EncodeFn)(CUtensorMap*, CUtensorMapDataType, cuuint32_t, void*, const cuuint64_t*, const cuuint64_t*, const cuuint32_t*, const cuuint32_t*,
                             CUtensorMapInterleave, CUtensorMapSwizzle, CUtensorMapL2promotion, CUtensorMapFloatOOBfill);

}

static void launch_on(void* const* d_in, void* d_out, cudaStream_t st) {
    static EncodeFn enc = nullptr;
    if (!enc) {
        cudaDriverEntryPointQueryResult qr;
        cudaGetDriverEntryPoint("cuTensorMapEncodeTiled", (void**)&enc, cudaEnableDefault, &qr);
        cudaFuncSetAttribute(fused_kernel, cudaFuncAttributeMaxDynamicSharedMemorySize, SMEM_BYTES);
    }
    Params p;
    CUtensorMap* maps[4] = {&p.mq, &p.mk, &p.mv, &p.mu};
    void* ptrs[4] = {d_in[0], d_in[1], d_in[2], d_in[6]};
    for (int i = 0; i < 4; i++) {
        cuuint64_t gd[3] = {448, 256, 8}, gs[2] = {7168, 896};
        cuuint32_t bx[3] = {16, 65, 8}, es[3] = {1, 1, 1};
        enc(maps[i], CU_TENSOR_MAP_DATA_TYPE_BFLOAT16, 3, ptrs[i], gd, gs, bx, es, CU_TENSOR_MAP_INTERLEAVE_NONE, CU_TENSOR_MAP_SWIZZLE_NONE,
            CU_TENSOR_MAP_L2_PROMOTION_NONE, CU_TENSOR_MAP_FLOAT_OOB_FILL_NONE);
    }
    const __nv_bfloat16* const* q = (const __nv_bfloat16* const*)d_in;
    p.shift_k = q[3]; p.ssm_k = q[4]; p.ssm_D = q[5];
    p.a_re = q[7]; p.a_im = q[8]; p.b_re = q[9]; p.b_im = q[10]; p.c_re = q[11]; p.c_im = q[12]; p.log_dt = q[13]; p.dskip = q[14];
    p.out = (__nv_bfloat16*)d_out;
    fused_kernel<<<112, 384, SMEM_BYTES, st>>>(p);
}

extern "C" void kernel_launch(void* const* d_in, const int* in_sizes, int n_in, void* d_out, int out_size) {
    launch_on(d_in, d_out, cudaStreamPerThread);
}
```

```cpp
#include <cuda_runtime.h>
#include <cuda_bf16.h>
#include <cuda.h>
#include <stdint.h>

namespace {

constexpr int XS = 4368;
constexpr int KS = 8320;
constexpr int PS = 4224;
constexpr int TBL = 28672;
constexpr int TBZ = TBL + 1344;
constexpr int O_PART = 2 * KS;
constexpr int O_KA = O_PART + 4 * PS;
constexpr int WGR = O_KA + 2 * KS;
constexpr int RAWB = 16640;
constexpr int O_YB = 0;
constexpr int O_YA = 16768;
constexpr int O_RV = 33536;
constexpr int O_RQ = 50176;
constexpr int O_XB = 66816;
constexpr int O_XA = O_XB + 4 * XS;
constexpr int O_WG = O_XA + 4 * XS + 128;
constexpr int O_PT = O_WG + 2 * WGR;
constexpr int O_BAR = O_PT + TBZ;
constexpr int SMEM_BYTES = O_BAR + 128;
static_assert(TBZ + 16384 <= WGR && SMEM_BYTES <= 232448, "smem");
enum { B_U = 0, B_KV = 8, B_Q = 16, B_S0 = 24, B_S1 = 32, B_XB0 = 40, B_XB1 = 48, B_XA = 56, B_YB = 64, B_YA = 72, B_KA0 = 80, B_KA1 = 88, B_K2 = 96, B_K3 = 104 };
#define HELP_POLLS 24
#define T_U 800
#define T_K 1200
constexpr int NHELP = 20;
constexpr int HELP_WG = 6;
constexpr int HELP_SMEM = HELP_WG * TBL + 512;

__device__ uint4 g_pkt[112 * 128];
__device__ unsigned g_cnt[224];

struct Params {
    CUtensorMap mu, mk, mv, mq;
    const __nv_bfloat16 *shift_k, *ssm_k, *ssm_D, *a_re, *a_im, *b_re, *b_im, *c_re, *c_im, *log_dt, *dskip;
    __nv_bfloat16* out;
};

#define STAMP(role, i)
#define KSTAMP(i)
#define TSARG
#define TSPASS
#define TSINIT(addr, off)
#define TSFLUSH(blk)

__device__ __forceinline__ uint32_t lds32(uint32_t a) { uint32_t v; asm volatile("ld.shared.u32 %0, [%1];" : "=r"(v) : "r"(a)); return v; }
__device__ __forceinline__ uint32_t lds16(uint32_t a) { uint16_t v; asm volatile("ld.shared.u16 %0, [%1];" : "=h"(v) : "r"(a)); return v; }
__device__ __forceinline__ uint2 lds64(uint32_t a) { uint2 v; asm volatile("ld.shared.v2.u32 {%0,%1}, [%2];" : "=r"(v.x), "=r"(v.y) : "r"(a)); return v; }
__device__ __forceinline__ uint4 lds128(uint32_t a) { uint4 v; asm volatile("ld.shared.v4.u32 {%0,%1,%2,%3}, [%4];" : "=r"(v.x), "=r"(v.y), "=r"(v.z), "=r"(v.w) : "r"(a)); return v; }
__device__ __forceinline__ void sts16(uint32_t a, uint32_t v) { asm volatile("st.shared.u16 [%0], %1;" ::"r"(a), "h"((uint16_t)v) : "memory"); }
__device__ __forceinline__ void sts32(uint32_t a, uint32_t v) { asm volatile("st.shared.u32 [%0], %1;" ::"r"(a), "r"(v) : "memory"); }
__device__ __forceinline__ void sts64(uint32_t a, uint32_t x, uint32_t y) { asm volatile("st.shared.v2.u32 [%0], {%1,%2};" ::"r"(a), "r"(x), "r"(y) : "memory"); }
__device__ __forceinline__ void sts128(uint32_t a, uint32_t x, uint32_t y, uint32_t z, uint32_t w) { asm volatile("st.shared.v4.u32 [%0], {%1,%2,%3,%4};" ::"r"(a), "r"(x), "r"(y), "r"(z), "r"(w) : "memory"); }
__device__ __forceinline__ uint32_t ldg16(const void* p) { uint16_t v; asm volatile("ld.global.nc.u16 %0, [%1];" : "=h"(v) : "l"(p)); return v; }
__device__ __forceinline__ uint32_t ldg32(const void* p) { uint32_t v; asm volatile("ld.global.nc.u32 %0, [%1];" : "=r"(v) : "l"(p)); return v; }
__device__ __forceinline__ uint2 ldg64(const void* p) { uint2 v; asm volatile("ld.global.nc.v2.u32 {%0,%1}, [%2];" : "=r"(v.x), "=r"(v.y) : "l"(p)); return v; }
__device__ __forceinline__ uint4 ldg128(const void* p) { uint4 v; asm volatile("ld.global.nc.v4.u32 {%0,%1,%2,%3}, [%4];" : "=r"(v.x), "=r"(v.y), "=r"(v.z), "=r"(v.w) : "l"(p)); return v; }
__device__ __forceinline__ uint32_t pack(float lo, float hi) { uint32_t r; asm("cvt.rn.bf16x2.f32 %0, %1, %2;" : "=r"(r) : "f"(hi), "f"(lo)); return r; }
__device__ __forceinline__ uint32_t hadd(uint32_t a, uint32_t b) { uint32_t r; asm("add.rn.bf16x2 %0, %1, %2;" : "=r"(r) : "r"(a), "r"(b)); return r; }
__device__ __forceinline__ uint32_t hmul(uint32_t a, uint32_t b) { uint32_t r; asm("mul.rn.bf16x2 %0, %1, %2;" : "=r"(r) : "r"(a), "r"(b)); return r; }
__device__ __forceinline__ uint32_t hfma(uint32_t a, uint32_t b, uint32_t c) { uint32_t r; asm("fma.rn.bf16x2 %0, %1, %2, %3;" : "=r"(r) : "r"(a), "r"(b), "r"(c)); return r; }
__device__ __forceinline__ uint32_t hneg(uint32_t a) { uint32_t r; asm("neg.bf16x2 %0, %1;" : "=r"(r) : "r"(a)); return r; }
__device__ __forceinline__ uint32_t prmt(uint32_t a, uint32_t b, uint32_t s) { uint32_t r; asm("prmt.b32 %0, %1, %2, %3;" : "=r"(r) : "r"(a), "r"(b), "r"(s)); return r; }
__device__ __forceinline__ float blo(uint32_t v) { return __uint_as_float(v << 16); }
__device__ __forceinline__ float bhi(uint32_t v) { return __uint_as_float(v & 0xffff0000u); }
__device__ __forceinline__ uint32_t mapa(uint32_t a, uint32_t r) { uint32_t o; asm("mapa.shared::cluster.u32 %0, %1, %2;" : "=r"(o) : "r"(a), "r"(r)); return o; }
__device__ __forceinline__ void st_async(uint32_t a, uint32_t x, uint32_t y, uint32_t z, uint32_t w, uint32_t bar) {
    asm volatile("st.async.weak.shared::cluster.mbarrier::complete_tx::bytes.v4.b32 [%0], {%1,%2,%3,%4}, [%5];" ::"r"(a), "r"(x), "r"(y), "r"(z), "r"(w), "r"(bar) : "memory");
}
__device__ __forceinline__ void wait_bar(uint32_t bar) {
    uint32_t done = 0;
    for (int it = 0; it < (1 << 22); it++) {
        asm volatile("{ .reg .pred p; mbarrier.try_wait.parity.acquire.cluster.shared::cta.b64 p, [%1], 0; selp.u32 %0, 1, 0, p; }" : "=r"(done) : "r"(bar) : "memory");
        if (done) break;
    }
}
__device__ __forceinline__ void bar_sync(int id, int n) { asm volatile("bar.sync %0, %1;" ::"r"(id), "r"(n) : "memory"); }
__device__ __forceinline__ bool bar_and(int id, bool v) {
    uint32_t r;
    asm volatile("{ .reg .pred p, q; setp.ne.u32 p, %2, 0; barrier.cta.red.and.aligned.pred q, %1, 128, p; selp.u32 %0, 1, 0, q; }" : "=r"(r) : "r"(id), "r"((uint32_t)v) : "memory");
    return r;
}
__device__ __forceinline__ void bar_arrive(int id, int n) { asm volatile("bar.arrive %0, %1;" ::"r"(id), "r"(n) : "memory"); }
__device__ __forceinline__ void tma3d(uint32_t dst, const CUtensorMap* m, int c0, int c1, uint32_t bar) {
    asm volatile("cp.async.bulk.tensor.3d.shared::cluster.global.mbarrier::complete_tx::bytes [%0], [%1, {%3, %4, %5}], [%2];" ::"r"(dst), "l"(m), "r"(bar), "r"(c0), "r"(c1), "r"(0) : "memory");
}

template <int OFF, int SC>
__device__ __forceinline__ void wgmma32(float (&d)[128], uint32_t a0, uint32_t a1, uint32_t a2, uint32_t a3, uint32_t dlo) {
    if constexpr (SC == 0)
    asm volatile("{ .reg .b64 dsc; mov.b64 dsc, {%20, 8};\n wgmma.mma_async.sync.aligned.m64n32k16.f32.bf16.bf16 {%0, %1, %2, %3, %4, %5, %6, %7, %8, %9, %10, %11, %12, %13, %14, %15}, {%16, %17, %18, %19}, dsc, 0, 1, 1, 0; }"
                 : "=f"(d[OFF + 0]), "=f"(d[OFF + 1]), "=f"(d[OFF + 2]), "=f"(d[OFF + 3]), "=f"(d[OFF + 4]), "=f"(d[OFF + 5]), "=f"(d[OFF + 6]), "=f"(d[OFF + 7]), "=f"(d[OFF + 8]), "=f"(d[OFF + 9]), "=f"(d[OFF + 10]), "=f"(d[OFF + 11]), "=f"(d[OFF + 12]), "=f"(d[OFF + 13]), "=f"(d[OFF + 14]), "=f"(d[OFF + 15])
                 : "r"(a0), "r"(a1), "r"(a2), "r"(a3), "r"(dlo));
    else
    asm volatile("{ .reg .b64 dsc; mov.b64 dsc, {%20, 8};\n wgmma.mma_async.sync.aligned.m64n32k16.f32.bf16.bf16 {%0, %1, %2, %3, %4, %5, %6, %7, %8, %9, %10, %11, %12, %13, %14, %15}, {%16, %17, %18, %19}, dsc, %21, 1, 1, 0; }"
                 : "+f"(d[OFF + 0]), "+f"(d[OFF + 1]), "+f"(d[OFF + 2]), "+f"(d[OFF + 3]), "+f"(d[OFF + 4]), "+f"(d[OFF + 5]), "+f"(d[OFF + 6]), "+f"(d[OFF + 7]), "+f"(d[OFF + 8]), "+f"(d[OFF + 9]), "+f"(d[OFF + 10]), "+f"(d[OFF + 11]), "+f"(d[OFF + 12]), "+f"(d[OFF + 13]), "+f"(d[OFF + 14]), "+f"(d[OFF + 15])
                 : "r"(a0), "r"(a1), "r"(a2), "r"(a3), "r"(dlo), "n"(SC));
}
#define WG_FENCE asm volatile("wgmma.fence.sync.aligned;" ::: "memory");
#define WG_COMMIT asm volatile("wgmma.commit_group.sync.aligned;" ::: "memory");
#define WG_WAIT(n) asm volatile("wgmma.wait_group.sync.aligned %0;" ::"n"(n) : "memory");

template <int J, int B, int NB>
__device__ __forceinline__ void step_ranges(float (&d)[128], uint32_t (&a)[32], uint32_t desc) {
    if constexpr (B < NB) {
        wgmma32<16 * B, J != 0>(d, a[4 * (J & 7)], a[4 * (J & 7) + 1], a[4 * (J & 7) + 2], a[4 * (J & 7) + 3], desc + (32 * B + 16 * J));
        step_ranges<J, B + 1, NB>(d, a, desc);
    }
}
template <int P>
__device__ __forceinline__ void group(float (&d)[128], uint32_t (&a)[32], uint32_t desc) {
    WG_FENCE
    step_ranges<2 * P, 0, 8 - P>(d, a, desc);
    step_ranges<2 * P + 1, 0, 8 - P>(d, a, desc);
    WG_COMMIT
}
template <int B>
__device__ __forceinline__ void epi(float (&d)[128], uint32_t& carry, uint32_t pw) {
    uint32_t r[4];
#pragma unroll
    for (int k = 3; k >= 0; k--) {
        const int i = 4 * B + k;
        r[k] = pack(d[4 * i], d[4 * i + 1]);
        if (i < 31) r[k] = hadd(r[k], carry);
        if (i > 0) carry = pack(d[4 * i + 2], d[4 * i + 3]);
    }
    asm volatile("stmatrix.sync.aligned.m8n8.x4.trans.shared.b16 [%0], {%1,%2,%3,%4};" ::"r"(pw - B * 512), "r"(r[0]), "r"(r[1]), "r"(r[2]), "r"(r[3]) : "memory");
}
template <int P>
__device__ __forceinline__ void loadA(uint32_t (&a)[32], uint32_t ax) {
#pragma unroll
    for (int j = 2 * P; j < 2 * P + 2; j++) {
        a[4 * (j & 7)] = lds32(ax + 256 * j);
        a[4 * (j & 7) + 1] = lds32(ax + 256 * j + 128);
        a[4 * (j & 7) + 2] = lds32(ax + 256 * j + 16);
        a[4 * (j & 7) + 3] = lds32(ax + 256 * j + 144);
    }
}
__device__ __forceinline__ void reduce_push(uint32_t pr, uint32_t dst0, uint32_t dst1, uint32_t bar0, uint32_t bar1) {
#pragma unroll
    for (int h = 0; h < 2; h++) {
        uint4 p0 = lds128(pr + h * 2048), p1 = lds128(pr + h * 2048 + PS), p2 = lds128(pr + h * 2048 + 2 * PS), p3 = lds128(pr + h * 2048 + 3 * PS);
        st_async(h ? dst1 : dst0, hadd(hadd(p0.x, p1.x), hadd(p2.x, p3.x)), hadd(hadd(p0.y, p1.y), hadd(p2.y, p3.y)),
                 hadd(hadd(p0.z, p1.z), hadd(p2.z, p3.z)), hadd(hadd(p0.w, p1.w), hadd(p2.w, p3.w)), h ? bar1 : bar0);
    }
}

struct C2 { uint32_t re, im; };
__device__ __forceinline__ C2 cmul(C2 a, uint32_t s) {
    C2 r;
    asm("{ .reg .b16 l, h; .reg .b32 sl, sh, t, u, v;\n mov.b32 {l, h}, %4; mov.b32 sl, {l, l}; mov.b32 sh, {h, h};\n"
        "mul.rn.bf16x2 t, %3, sh; mul.bf16x2 u, %2, sl; sub.bf16x2 %0, u, t;\n"
        "mul.rn.bf16x2 v, %3, sl; fma.rn.bf16x2 %1, %2, sh, v; }" : "=r"(r.re), "=r"(r.im) : "r"(a.re), "r"(a.im), "r"(s));
    return r;
}
__device__ __forceinline__ void csq(float& re, float& im) { float t = re + re; re = fmaf(re, re, -im * im); im = t * im; }
__device__ __forceinline__ float ex2(float x) { float r; asm("ex2.approx.ftz.f32 %0, %1;" : "=f"(r) : "f"(x)); return r; }
__device__ __forceinline__ void st2(uint32_t are, uint32_t aim, C2 a, C2 b, C2 c, C2 d) { sts128(are, a.re, b.re, c.re, d.re); sts128(aim, a.im, b.im, c.im, d.im); }
struct KParams { uint32_t p[6], ldt, dsk; };
__device__ __forceinline__ void kgen_load(KParams& k, const Params& prm, int ch, int tid) {
    const size_t po = (size_t)ch * 256 + tid * 2;
    k.ldt = ldg16(prm.log_dt + ch);
    k.p[0] = ldg32(prm.a_re + po); k.p[1] = ldg32(prm.a_im + po); k.p[2] = ldg32(prm.b_re + po);
    k.p[3] = ldg32(prm.b_im + po); k.p[4] = ldg32(prm.c_re + po); k.p[5] = ldg32(prm.c_im + po);
    k.dsk = ldg16(prm.dskip + ch);
}
template <int SC>
__device__ __forceinline__ void wgmma48(float (&d)[24], uint32_t da, uint32_t db) {
    if constexpr (SC == 0)
        asm volatile("{ .reg .b64 da, db; mov.b64 da, {%24, 128}; mov.b64 db, {%25, 128};\n wgmma.mma_async.sync.aligned.m64n48k16.f32.bf16.bf16 {%0,%1,%2,%3,%4,%5,%6,%7,%8,%9,%10,%11,%12,%13,%14,%15,%16,%17,%18,%19,%20,%21,%22,%23}, da, db, 0, 1, 1, 1, 1; }"
                     : "=f"(d[0]), "=f"(d[1]), "=f"(d[2]), "=f"(d[3]), "=f"(d[4]), "=f"(d[5]), "=f"(d[6]), "=f"(d[7]), "=f"(d[8]), "=f"(d[9]), "=f"(d[10]), "=f"(d[11]), "=f"(d[12]), "=f"(d[13]), "=f"(d[14]), "=f"(d[15]), "=f"(d[16]), "=f"(d[17]), "=f"(d[18]), "=f"(d[19]), "=f"(d[20]), "=f"(d[21]), "=f"(d[22]), "=f"(d[23]) : "r"(da), "r"(db));
    else
        asm volatile("{ .reg .b64 da, db; mov.b64 da, {%24, 128}; mov.b64 db, {%25, 128};\n wgmma.mma_async.sync.aligned.m64n48k16.f32.bf16.bf16 {%0,%1,%2,%3,%4,%5,%6,%7,%8,%9,%10,%11,%12,%13,%14,%15,%16,%17,%18,%19,%20,%21,%22,%23}, da, db, 1, 1, 1, 1, 1; }"
                     : "+f"(d[0]), "+f"(d[1]), "+f"(d[2]), "+f"(d[3]), "+f"(d[4]), "+f"(d[5]), "+f"(d[6]), "+f"(d[7]), "+f"(d[8]), "+f"(d[9]), "+f"(d[10]), "+f"(d[11]), "+f"(d[12]), "+f"(d[13]), "+f"(d[14]), "+f"(d[15]), "+f"(d[16]), "+f"(d[17]), "+f"(d[18]), "+f"(d[19]), "+f"(d[20]), "+f"(d[21]), "+f"(d[22]), "+f"(d[23]) : "r"(da), "r"(db));
}
__device__ __forceinline__ void wait48(float (&d)[24]) {
    asm volatile("wgmma.wait_group.sync.aligned 0;" : "+f"(d[0]), "+f"(d[1]), "+f"(d[2]), "+f"(d[3]), "+f"(d[4]), "+f"(d[5]), "+f"(d[6]), "+f"(d[7]), "+f"(d[8]), "+f"(d[9]), "+f"(d[10]), "+f"(d[11]), "+f"(d[12]), "+f"(d[13]), "+f"(d[14]), "+f"(d[15]), "+f"(d[16]), "+f"(d[17]), "+f"(d[18]), "+f"(d[19]), "+f"(d[20]), "+f"(d[21]), "+f"(d[22]), "+f"(d[23]) :: "memory");
}
__device__ __forceinline__ void kext(float (&v)[6], const float (&d)[24]) {
    v[0] = d[0] - d[14]; v[1] = d[1] - d[15]; v[2] = d[4] - d[18]; v[3] = d[5] - d[19]; v[4] = d[8] - d[22]; v[5] = d[9] - d[23];
}
template <int PDB, bool EXT>
__device__ __forceinline__ void kgen_batch(const KParams& k, int b, uint32_t gb, int tid, int barid, float (&d)[24], float (&v)[6] TSARG) {
    const float dt = __bfloat162float(__float2bfloat16_rn(expf(blo(k.ldt))));
    const float dl = dt * 1.4426950408889634f;
    const uint32_t tb = gb + tid * 16, tp = tb + b * PDB;
    const uint32_t dsc = ((gb & 0x3FFFF) >> 4) | 0x80000, dsp = dsc + b * (PDB / 16);
    const uint32_t sel = b ? 0x3244 : 0x1044;
    const float al = __uint_as_float(prmt(k.p[0], 0, sel)) * dl, om = __uint_as_float(prmt(k.p[1], 0, sel)) * dt;
    const float br = __uint_as_float(prmt(k.p[2], 0, sel)) * dt, bi = __uint_as_float(prmt(k.p[3], 0, sel)) * dt;
    const float cr = __uint_as_float(prmt(k.p[4], 0, sel)), ci = __uint_as_float(prmt(k.p[5], 0, sel));
    const float wr = fmaf(cr, br, -ci * bi), wi = fmaf(cr, bi, ci * br);
    const float r1 = ex2(al), r64 = ex2(al * 64.f);
    float re = r1 * __cosf(om), im = r1 * __sinf(om);
    float hr = r64 * __cosf(om * 64.f), hi = r64 * __sinf(om * 64.f);
    const uint32_t s1 = pack(re, im);
    csq(re, im);
    const uint32_t s2 = pack(re, im);
    csq(re, im);
    C2 qa; qa.re = pack(wr, fmaf(wr, re, -wi * im)); qa.im = pack(wi, fmaf(wr, im, wi * re));
    csq(re, im);
    C2 p0; p0.re = pack(1.f, re); p0.im = pack(0.f, im);
    csq(re, im);
    const uint32_t s16 = pack(re, im);
    csq(re, im);
    const uint32_t s32 = pack(re, im);
    const uint32_t s64 = pack(hr, hi);
    csq(hr, hi);
    const uint32_t s128 = pack(hr, hi);
    csq(hr, hi);
    const uint32_t s256 = pack(hr, hi);
    csq(hr, hi);
    const uint32_t s512 = pack(hr, hi);
    csq(hr, hi);
    const uint32_t s1024 = pack(hr, hi);
    if (PDB == 0) { if (EXT) { wait48(d); kext(v, d); } bar_sync(barid, 128); }
    const C2 p1 = cmul(p0, s16), p2 = cmul(p0, s32), p3 = cmul(p1, s32);
    st2(tp, tp + 2048, p0, p1, p2, p3);
    st2(tp + 8192, tp + 10240, cmul(p0, s128), cmul(p1, s128), cmul(p2, s128), cmul(p3, s128));
    const C2 p4 = cmul(p0, s64), p5 = cmul(p1, s64), p6 = cmul(p2, s64), p7 = cmul(p3, s64);
    st2(tp + 4096, tp + 6144, p4, p5, p6, p7);
    st2(tp + 12288, tp + 14336, cmul(p4, s128), cmul(p5, s128), cmul(p6, s128), cmul(p7, s128));
    if (PDB != 0) { if (EXT) { wait48(d); kext(v, d); } bar_sync(barid, 128); }
    KSTAMP(17 + 3 * b);
    const C2 qb = cmul(qa, s2), qg = cmul(qa, s512);
    st2(tb + 16384, tb + 22528, qa, qb, cmul(qa, s1), cmul(qb, s1));
    st2(tb + 18432, tb + 24576, cmul(qa, s256), cmul(qb, s256), qg, cmul(qg, s256));
    C2 qf; qf.re = prmt(qa.re, qg.re, 0x5410); qf.im = prmt(qa.im, qg.im, 0x5410);
    const C2 qh = cmul(qf, s1024), qi = cmul(qh, s1024);
    st2(tb + 20480, tb + 26624, qh, cmul(qh, s256), qi, qi);
    asm volatile("fence.proxy.async.shared::cta;" ::: "memory");
    bar_sync(barid, 128);
    KSTAMP(18 + 3 * b);
    WG_FENCE
    wgmma48<0>(d, dsp, dsc + 1024);
#pragma unroll
    for (int s = 1; s < 8; s++) wgmma48<1>(d, dsp + 16 * s, dsc + 1024 + 16 * s);
    WG_COMMIT
}
__device__ __forceinline__ void kgen_end(const KParams& k, int tid, const float (&d)[24], const float (&v)[6], uint32_t (&o)[3]) {
    float u[6];
    kext(u, d);
    if (tid == 0) u[0] += blo(k.dsk);
    o[0] = pack(u[0] + v[0], u[1] + v[1]); o[1] = pack(u[2] + v[2], u[3] + v[3]); o[2] = pack(u[4] + v[4], u[5] + v[5]);
}
template <int PDB>
__device__ __forceinline__ void kgen(const KParams& k, uint32_t gb, int tid, int barid, uint32_t (&o)[3] TSARG) {
    float d[24], v[6];
#pragma unroll
    for (int i = 0; i < 24; i++) asm volatile("" : "=f"(d[i]));
#pragma unroll 1
    for (int b = 0; b < 2; b++) kgen_batch<PDB, true>(k, b, gb, tid, barid, d, v TSPASS);
    wait48(d);
    kgen_end(k, tid, d, v, o);
    KSTAMP(22);
}
__device__ __forceinline__ void kexpand(const uint32_t (&o)[3], uint32_t zb, uint32_t ke, int w, int lane, int barid) {
    {
        const int t = lane & 3, b = 8 * w + (lane >> 2);
        const uint32_t z0 = zb + 16 * b + 4 * (t & 1) + (t & 2);
        const uint32_t z1 = zb + (t < 2 ? 512 + 8 * b + 2 * t : 512 + 128 * t + 4 * b);
        const uint32_t z2 = zb + 1024 + (t == 2 ? 256 : 64 * t) + 2 * b;
        sts16(z0, o[0]); sts16(z0 + 8, o[0] >> 16);
        sts16(z1, o[1]); sts16(z1 + (t < 2 ? 4 : 2), o[1] >> 16);
        if (t < 3) sts16(z2, o[2]);
        if (t < 2) sts16(z2 + 128, o[2] >> 16);
    }
    bar_sync(barid, 128);
    uint32_t e0, e1, e2, e3, o0, o1, o2, o3;
    if (w == 0) {
        const uint4 e = lds128(zb + lane * 16);
        const uint32_t p = lane ? lds32(zb + lane * 16 - 4) : 0;
        e0 = e.x; e1 = e.y; e2 = e.z; e3 = e.w;
        o0 = prmt(p, e.x, 0x5432); o1 = prmt(e.x, e.y, 0x5432); o2 = prmt(e.y, e.z, 0x5432); o3 = prmt(e.z, e.w, 0x5432);
    } else if (w == 1) {
        const uint2 v = lds64(zb + 512 + lane * 8);
        const uint32_t v4 = lds32(zb + 512 + lane * 8 + 8), pv = lds32(zb + 508);
        e0 = prmt(v.x, 0, 0x1010); e1 = prmt(v.x, v.y, 0x5432); e2 = prmt(v.y, 0, 0x1010); e3 = prmt(v.y, v4, 0x5432);
        o0 = lane ? e0 : prmt(pv, v.x, 0x5432); o1 = v.x; o2 = e2; o3 = v.y;
    } else {
        const uint32_t za = zb + 768 + ((w - 2) * 32 + lane) * 4;
        const uint32_t v = lds32(za), v2 = lds32(za + 4);
        e0 = prmt(v, 0, 0x1010); e1 = v; e2 = prmt(v, 0, 0x3232); e3 = prmt(v2, 0, 0x1010);
        o0 = e0; o1 = e0; o2 = e2; o3 = prmt(v, v2, 0x5432);
    }
    const uint32_t za = zb + 1024 + (w * 32 + lane) * 2;
    const uint32_t v0 = lds16(za), v1 = lds16(za + 2);
    if (w == 3 && lane < 2) sts128(ke + lane * 4160, 0, 0, 0, 0);
    ke += 16 + w * 512 + lane * 16;
    sts128(ke, e0, e1, e2, e3);
    sts128(ke + 4160, o0, o1, o2, o3);
    const uint32_t d0 = v0 * 0x10001u, d1 = v1 * 0x10001u, m = v0 | (v1 << 16);
    sts128(ke + 2048, d0, d0, (lane & 1) ? d1 : m, d1);
    sts128(ke + 2048 + 4160, d0, d0, (lane & 1) ? m : d0, d1);
}

template <bool GATE>
__device__ __forceinline__ void final_pass(uint32_t ybase, uint32_t qbase, __nv_bfloat16* outp, int w, int nw, int lane) {
    const int r = lane & 7, k = lane >> 3, g = lane >> 2, t = lane & 3;
    const int ch = 8 * ((r >> 1) & 1) + 2 * k + (r & 1);
    const uint32_t ya = ybase + ch * 1040 + (ch >> 3) * 64 + (r >> 2) * 32;
    const uint32_t qa = qbase + g * 2080 + (2 * (t >> 1) + 1) * 32 + (t & 1) * 16;
    char* op = (char*)outp + (size_t)(16 * (t >> 1) + g) * 1792 + (t & 1) * 16;
#pragma unroll 2
    for (int i = w; i < 32; i += nw) {
        const int c = (i & 1) + 4 * (i >> 1);
        uint32_t v0, v1, v2, v3;
        asm volatile("ldmatrix.sync.aligned.m8n8.x4.trans.shared.b16 {%0,%1,%2,%3}, [%4];" : "=r"(v0), "=r"(v1), "=r"(v2), "=r"(v3) : "r"(ya + c * 16));
        if (GATE) {
            uint4 q = lds128(qa + c * 32);
            v0 = hmul(v0, q.x); v1 = hmul(v1, q.y); v2 = hmul(v2, q.z); v3 = hmul(v3, q.w);
        }
        asm volatile("st.global.v4.b32 [%0], {%1,%2,%3,%4};" ::"l"(op + (size_t)c * (8 * 1792)), "r"(v0), "r"(v1), "r"(v2), "r"(v3) : "memory");
    }
}

__device__ __forceinline__ void push4(uint32_t dd, const uint32_t (&R)[8], uint32_t bx) {
    st_async(dd, prmt(R[7], R[6], 0x5410), prmt(R[5], R[4], 0x5410), prmt(R[3], R[2], 0x5410), prmt(R[1], R[0], 0x5410), bx);
    st_async(dd + XS, prmt(R[7], R[6], 0x7632), prmt(R[5], R[4], 0x7632), prmt(R[3], R[2], 0x7632), prmt(R[1], R[0], 0x7632), bx);
}
__device__ __forceinline__ void expect_tx(uint32_t bar, uint32_t n) { asm volatile("mbarrier.arrive.expect_tx.shared.b64 _, [%0], %1;" ::"r"(bar), "r"(n) : "memory"); }
__device__ __forceinline__ void bulk_g2s(uint32_t dst, const void* src, uint32_t n, uint32_t bar) {
    asm volatile("cp.async.bulk.shared::cluster.global.mbarrier::complete_tx::bytes [%0], [%1], %2, [%3];" ::"r"(dst), "l"(src), "r"(n), "r"(bar) : "memory");
}

__device__ __forceinline__ void warp_arrive(uint32_t bar, int lane) {
    __syncwarp();
    if (lane == 0) asm volatile("mbarrier.arrive.shared.b64 _, [%0];" ::"r"(bar) : "memory");
}

__global__ void __cluster_dims__(4, 1, 1) __launch_bounds__(384, 1) fused_kernel(const __grid_constant__ Params prm) {
    extern __shared__ __align__(1024) char smem[];
    asm volatile("griddepcontrol.launch_dependents;");
    const uint32_t base = (uint32_t)__cvta_generic_to_shared(smem);
    const uint32_t bars = base + O_BAR;
    const int wg = __shfl_sync(0xffffffff, threadIdx.x >> 7, 0);
    const int tid = threadIdx.x & 127, lane = threadIdx.x & 31;
    const int w = __shfl_sync(0xffffffff, tid >> 5, 0);
    const int rank = blockIdx.x & 3, cl = blockIdx.x >> 2;
    const int ch0 = 4 * blockIdx.x;
    __nv_bfloat16* const ob = prm.out + (size_t)(512 * rank) * 896 + 16 * cl;
    TSINIT(base + (wg == 0 ? O_YB + 16688 : wg == 1 ? O_YA + 16688 : O_YB + 16736), wg == 2 ? O_YA - 32 : 0)
    KParams kp;
    if (wg == 2) {
        const int c4 = tid & 3, gam = tid >> 2;
        const unsigned t0 = clock();
        if (w == 1 && lane < 28) {
            const __nv_bfloat16* pp = lane < 4 ? prm.a_re : lane < 8 ? prm.a_im : lane < 12 ? prm.b_re : lane < 16 ? prm.b_im : lane < 20 ? prm.c_re : prm.c_im;
            if (lane < 24) asm volatile("prefetch.global.L2 [%0];" ::"l"(pp + (ch0 + 3) * 256 + (lane & 3) * 64) : "memory");
            else asm volatile("prefetch.tensormap [%0];" ::"l"(&prm.mu + (lane - 24)) : "memory");
        }
        kgen_load(kp, prm, ch0 + 2, tid);
        const uint4 s0 = ldg128(prm.shift_k + (16 * cl + 4 * c4) * 4), s1 = ldg128(prm.shift_k + (16 * cl + 4 * c4) * 4 + 8);
        const uint32_t dA = ldg32(prm.ssm_D + ch0 + (w & 2));
        if (tid == 0) {
#pragma unroll
            for (int i = 0; i < 14; i++) asm volatile("mbarrier.init.shared.b64 [%0], %1;" ::"r"(bars + 8 * i), "r"(i < 10 ? 1 : 4) : "memory");
            asm volatile("fence.mbarrier_init.release.cluster;" ::: "memory");
            asm volatile("fence.proxy.async.shared::cta;" ::: "memory");
            expect_tx(bars + B_U, RAWB);
            expect_tx(bars + B_KV, 2 * RAWB); expect_tx(bars + B_Q, RAWB); expect_tx(bars + B_S0, 8192); expect_tx(bars + B_S1, 8192);
            expect_tx(bars + B_XB0, 8192); expect_tx(bars + B_XB1, 8192); expect_tx(bars + B_XA, 16384);
            expect_tx(bars + B_YB, 16384); expect_tx(bars + B_YA, 16384);
        }
        __syncwarp();
        asm volatile("barrier.cluster.arrive.relaxed.aligned;" ::: "memory");
        if (tid == 0) {
            while (clock() - t0 < T_U) {}
            tma3d(base + O_YB, &prm.mu, 16 * cl, 64 * rank - 1, bars + B_U);
            while (clock() - t0 < T_K) {}
            tma3d(base + O_YA, &prm.mk, 16 * cl, 64 * rank - 1, bars + B_KV);
            tma3d(base + O_RV, &prm.mv, 16 * cl, 64 * rank - 1, bars + B_KV);
#pragma unroll
            for (int i = 0; i < 4; i++)
                asm volatile("cp.async.bulk.prefetch.L2.global [%0], %1;" ::"l"(prm.ssm_k + (size_t)(ch0 + 2 * (i & 1) + (i >> 1)) * 2048), "r"(4096) : "memory");
            tma3d(base + O_RQ, &prm.mq, 16 * cl, 64 * rank - 1, bars + B_Q);
        }
        __syncwarp();
        asm volatile("setmaxnreg.dec.sync.aligned.u32 104;");
        asm volatile("barrier.cluster.wait.acquire.aligned;" ::: "memory");
        STAMP(2, 0);
        const uint32_t roff = (gam + 1) * 32 + c4 * 8;
        const uint32_t xdst = mapa(base + 32 * c4 + 16 * (255 - 64 * rank - gam), c4);
        wait_bar(bars + B_U);
        STAMP(2, 1);
        {
            uint32_t Rx[2][8], Ry[2][8];
#pragma unroll
            for (int pass = 0; pass < 2; pass++)
#pragma unroll
                for (int i = 0; i < 8; i++) { uint2 v = lds64(base + O_YB + roff + pass * 1024 + i * 2080); Rx[pass][i] = v.x; Ry[pass][i] = v.y; }
            const uint32_t bx = mapa(bars + B_XB0, c4);
            push4(xdst + O_XB, Rx[0], bx);
            push4(xdst + O_XB - 512, Rx[1], bx);
            push4(xdst + O_XB + 2 * XS, Ry[0], bx + 8);
            push4(xdst + O_XB + 2 * XS - 512, Ry[1], bx + 8);
        }
        STAMP(2, 2);
        unsigned tag = 0;
#pragma unroll 1
        for (int job = 0; job < 2; job++) {
            uint32_t o[3];
            bool local = true;
            if (job) {
                tag++;
                if (tid == 0) g_cnt[blockIdx.x] = tag;
                bool ok = false;
#pragma unroll 1
                for (int it = 0; it < HELP_POLLS && !ok; it++) {
                    uint32_t tg;
                    asm volatile("{ .reg .b128 v; .reg .b64 l, h; ld.relaxed.gpu.global.b128 v, [%4]; mov.b128 {l, h}, v; mov.b64 {%0, %1}, l; mov.b64 {%2, %3}, h; }"
                                 : "=r"(o[0]), "=r"(o[1]), "=r"(o[2]), "=r"(tg) : "l"(g_pkt + blockIdx.x * 128 + tid) : "memory");
                    ok = tg == tag;
                }
                local = !bar_and(6, ok);
                if (local) kgen_load(kp, prm, ch0 + 3, tid);
                STAMP(2, 9);
            }
            if (local) {
                float v[6];
#pragma unroll 1
                for (int b = 0; b < 2; b++) {
                    float d[24];
                    kgen_batch<0, false>(kp, b, base + O_PT, tid, 6, d, v TSPASS);
                    wait48(d);
                    if (b) { kgen_end(kp, tid, d, v, o); break; }
                    kext(v, d);
                    if (job) continue;
                    STAMP(2, 3);
                    uint32_t W[4][2];
                    W[0][0] = prmt(s0.x, s0.z, 0x5410); W[1][0] = prmt(s0.x, s0.z, 0x7632); W[2][0] = prmt(s0.y, s0.w, 0x5410); W[3][0] = prmt(s0.y, s0.w, 0x7632);
                    W[0][1] = prmt(s1.x, s1.z, 0x5410); W[1][1] = prmt(s1.x, s1.z, 0x7632); W[2][1] = prmt(s1.y, s1.w, 0x5410); W[3][1] = prmt(s1.y, s1.w, 0x7632);
                    wait_bar(bars + B_KV);
                    STAMP(2, 4);
                    const uint32_t bx = mapa(bars + B_XA, c4);
#pragma unroll 1
                    for (int pass = 0; pass < 2; pass++) {
                        const uint32_t kb = base + O_YA + roff + pass * 1024, vb = base + O_RV + roff + pass * 1024;
                        uint2 k3 = lds64(kb - 32 + 5 * 2080), k2 = lds64(kb - 32 + 6 * 2080), k1 = lds64(kb - 32 + 7 * 2080);
                        uint32_t Rx[8], Ry[8];
#pragma unroll
                        for (int i = 0; i < 8; i++) {
                            uint2 k0 = lds64(kb + i * 2080), v = lds64(vb + i * 2080);
                            Rx[i] = hmul(hfma(k0.x, W[0][0], hfma(k1.x, W[1][0], hfma(k2.x, W[2][0], hmul(k3.x, W[3][0])))), v.x);
                            Ry[i] = hmul(hfma(k0.y, W[0][1], hfma(k1.y, W[1][1], hfma(k2.y, W[2][1], hmul(k3.y, W[3][1])))), v.y);
                            k3 = k2; k2 = k1; k1 = k0;
                        }
                        push4(xdst + O_XA - pass * 512, Rx, bx);
                        push4(xdst + O_XA + 2 * XS - pass * 512, Ry, bx);
                    }
                    STAMP(2, 5);
#pragma unroll 1
                    for (int st = 0; st < 2; st++) {
                        const uint32_t ka = base + O_WG + (w >> 1) * WGR + O_KA + st * KS + 16 + (w & 1) * 2048 + lane * 16;
                        wait_bar(bars + B_S0 + 8 * st);
                        uint4 e[4];
                        uint32_t p[4];
#pragma unroll
                        for (int i = 0; i < 4; i++) { e[i] = lds128(ka + i * 512); p[i] = lds32(ka + i * 512 - 4); }
                        if ((w & 1) == 0 && lane == 0) {
                            e[0].x = (e[0].x & 0xffff0000u) | (pack(blo(e[0].x) + (st ? bhi(dA) : blo(dA)), 0.f) & 0xffffu);
                            sts32(ka, e[0].x);
                        }
#pragma unroll
                        for (int i = 0; i < 4; i++)
                            sts128(ka + i * 512 + 4160, prmt(p[i], e[i].x, 0x5432), prmt(e[i].x, e[i].y, 0x5432), prmt(e[i].y, e[i].z, 0x5432), prmt(e[i].z, e[i].w, 0x5432));
                        warp_arrive(bars + B_KA0 + 8 * st, lane);
                        STAMP(2, 6 + st);
                    }
                    tag = *(volatile unsigned*)&g_cnt[blockIdx.x];
                }
            }
            kexpand(o, base + O_PT + TBL, base + O_WG + job * WGR + KS, w, lane, 6);
            warp_arrive(bars + B_K2 + 8 * job, lane);
            STAMP(2, 8 + 2 * job);
        }
        wait_bar(bars + B_Q);
        wait_bar(bars + B_YA);
        STAMP(wg, 11);
        final_pass<true>(base + O_YA, base + O_RQ, ob, w, 4, lane);
        STAMP(wg, 12);
    } else {
        kgen_load(kp, prm, ch0 + wg, tid);
        asm volatile("barrier.cluster.arrive.relaxed.aligned;" ::: "memory");
        const int g = lane >> 2, t = lane & 3;
        const uint32_t wgb = base + O_WG + wg * WGR;
        const uint32_t xb = base + O_XB + 32 * rank;
        if (lane < 17) sts128(xb + (w < 2 ? wg + 2 * w : 2 + 2 * wg + w) * XS + 4096 + lane * 16, 0, 0, 0, 0);
        const uint32_t aoff = wgb + 16 + ((g & 1) ? 0 : 4160) + 4 * (8 * w + t + (g >> 1) - 3);
        const uint32_t pw = wgb + O_PART + w * PS + 16 * (255 + 2 * w - lane);
        const uint32_t pr = wgb + O_PART + tid * 16;
        const uint32_t yloc = base + (4 * rank * 1040 + (rank >> 1) * 64) + (tid & 63) * 16;
        const uint32_t y0 = mapa(yloc, w >> 1), yb0 = mapa(bars, w >> 1);
        const uint32_t ystep = mapa(yloc, 2 + (w >> 1)) - y0;
        asm volatile("barrier.cluster.wait.acquire.aligned;" ::: "memory");
        STAMP(wg, 0);
        {
            uint32_t o[3];
            kgen<TBL>(kp, wgb, tid, 1 + wg, o TSPASS);
            kexpand(o, wgb + TBL + 16384, wgb, w, lane, 1 + wg);
            if (lane < 2 * w) sts128(wgb + O_PART + w * PS + lane * 16, 0, 0, 0, 0);
            asm volatile("fence.proxy.async.shared::cta;" ::: "memory");
            bar_sync(1 + wg, 128);
            if (w < 2 && lane == 0) {
                const uint32_t ka = wgb + O_KA + w * KS;
                asm volatile("fence.proxy.async.shared::cta;" ::: "memory");
                bulk_g2s(ka + 16, prm.ssm_k + (size_t)(ch0 + 2 * wg + w) * 2048, 4096, bars + B_S0 + 8 * w);
                sts128(ka, 0, 0, 0, 0);
                sts128(ka + 4160, 0, 0, 0, 0);
            }
            __syncwarp();
        }
        asm volatile("setmaxnreg.inc.sync.aligned.u32 200;");
        STAMP(wg, 1);
        float d[128];
        uint32_t a[32];
        uint32_t carry = 0;
        bool pref = false;
        uint32_t yo = 0, bo = 0;
        uint32_t axc = aoff;
#pragma unroll 1
        for (int c = 0; c < 4; c++) {
            const bool isB = (c == 0) | (c == 3);
            const int chl = isB ? (c ? 2 + wg : wg) : c - 1 + 2 * wg;
            const uint32_t axn = aoff + (c == 2 ? KS : O_KA + c * KS);
            const uint32_t kbar = bars + B_KA0 + 8 * c + (c == 2 ? 8 * wg : 0);
            if (!pref) { loadA<0>(a, axc); loadA<1>(a, axc); loadA<2>(a, axc); loadA<3>(a, axc); }
            if (c != 2) {
                wait_bar(bars + (c == 0 ? B_XB0 : isB ? B_XB1 : B_XA));
                asm volatile("fence.proxy.async.shared::cta;" ::: "memory");
            }
            STAMP(wg, 2 + 2 * c);
            const uint32_t xa = xb + (isB ? chl : 4 + chl) * XS;
            const uint32_t desc = ((xa & 0x3FFFF) >> 4) | 0x10000;
            group<0>(d, a, desc);
            if (c) {
                bar_sync(1 + wg, 128);
                reduce_push(pr, y0 + yo, y0 + ystep + yo, yb0 + bo, yb0 + ystep + bo);
            }
            group<1>(d, a, desc);
            bar_sync(1 + wg, 128);
            yo = (isB ? O_YB : O_YA) + chl * 1040;
            bo = isB ? B_YB : B_YA;
#define STAGE(P) WG_WAIT(1) epi<7 - P>(d, carry, pw);
            STAGE(0) loadA<4>(a, axc); group<2>(d, a, desc);
            STAGE(1) loadA<5>(a, axc); group<3>(d, a, desc);
            STAGE(2) loadA<6>(a, axc); group<4>(d, a, desc);
            STAGE(3) loadA<7>(a, axc); group<5>(d, a, desc);
            {
                uint32_t done;
                asm volatile("{ .reg .pred p; mbarrier.test_wait.parity.shared::cta.b64 p, [%1], 0; selp.u32 %0, 1, 0, p; }" : "=r"(done) : "r"(kbar) : "memory");
                pref = __all_sync(0xffffffff, done) && c < 3;
            }
            STAGE(4) if (pref) loadA<0>(a, axn); group<6>(d, a, desc);
            STAGE(5) if (pref) loadA<1>(a, axn); group<7>(d, a, desc);
            STAGE(6) if (pref) loadA<2>(a, axn);
            WG_WAIT(0) epi<0>(d, carry, pw); if (pref) loadA<3>(a, axn);
            axc = axn;
            STAMP(wg, 3 + 2 * c);
            if (!pref && c < 3) wait_bar(kbar);
        }
        bar_sync(1 + wg, 128);
        reduce_push(pr, y0 + yo, y0 + ystep + yo, yb0 + bo, yb0 + ystep + bo);
        STAMP(wg, 10);
    }
    wait_bar(bars + B_YB);
    STAMP(wg, 13);
    final_pass<false>(base + O_YB, 0, ob + 448, 4 * wg + w, 12, lane);
    STAMP(wg, 14);
    TSFLUSH(blockIdx.x);
}

__global__ void __launch_bounds__(128 * HELP_WG, 1) helper_kernel(const __grid_constant__ Params prm) {
    extern __shared__ __align__(1024) char smem[];
    const uint32_t base = (uint32_t)__cvta_generic_to_shared(smem);
    const int grp = __shfl_sync(0xffffffff, threadIdx.x >> 7, 0);
    const int tid = threadIdx.x & 127;
    const int hi = grp * NHELP + blockIdx.x;
    TSINIT(base + HELP_WG * TBL + grp * 64, 0)
    KParams kp;
    if (hi < 112) {
        kgen_load(kp, prm, 4 * hi + 3, tid);
        unsigned tag = *(volatile unsigned*)&g_cnt[112 + hi];
        uint32_t o[3];
        kgen<0>(kp, base + grp * TBL, tid, 1 + grp, o TSPASS);
        tag++;
        if (tid == 0) g_cnt[112 + hi] = tag;
        asm volatile("{ .reg .b128 v; .reg .b64 l, h; mov.b64 l, {%0, %1}; mov.b64 h, {%2, %3}; mov.b128 v, {l, h}; st.relaxed.gpu.global.b128 [%4], v; }"
                     ::"r"(o[0]), "r"(o[1]), "r"(o[2]), "r"(tag), "l"(g_pkt + hi * 128 + tid) : "memory");
        STAMP(0, 23);
        TSFLUSH(112 + blockIdx.x);
    }
}

typedef CUresult (*EncodeFn)(CUtensorMap*, CUtensorMapDataType, cuuint32_t, void*, const cuuint64_t*, const cuuint64_t*, const cuuint32_t*, const cuuint32_t*,
                             CUtensorMapInterleave, CUtensorMapSwizzle, CUtensorMapL2promotion, CUtensorMapFloatOOBfill);

}

static void launch_on(void* const* d_in, void* d_out, cudaStream_t st) {
    static EncodeFn enc = nullptr;
    if (!enc) {
        cudaDriverEntryPointQueryResult qr;
        cudaGetDriverEntryPoint("cuTensorMapEncodeTiled", (void**)&enc, cudaEnableDefault, &qr);
        cudaFuncSetAttribute(fused_kernel, cudaFuncAttributeMaxDynamicSharedMemorySize, SMEM_BYTES);
        cudaFuncSetAttribute(helper_kernel, cudaFuncAttributeMaxDynamicSharedMemorySize, HELP_SMEM);
    }
    Params p;
    CUtensorMap* maps[4] = {&p.mq, &p.mk, &p.mv, &p.mu};
    void* ptrs[4] = {d_in[0], d_in[1], d_in[2], d_in[6]};
    for (int i = 0; i < 4; i++) {
        cuuint64_t gd[3] = {448, 256, 8}, gs[2] = {7168, 896};
        cuuint32_t bx[3] = {16, 65, 8}, es[3] = {1, 1, 1};
        enc(maps[i], CU_TENSOR_MAP_DATA_TYPE_BFLOAT16, 3, ptrs[i], gd, gs, bx, es, CU_TENSOR_MAP_INTERLEAVE_NONE, CU_TENSOR_MAP_SWIZZLE_NONE,
            CU_TENSOR_MAP_L2_PROMOTION_NONE, CU_TENSOR_MAP_FLOAT_OOB_FILL_NONE);
    }
    const __nv_bfloat16* const* q = (const __nv_bfloat16* const*)d_in;
    p.shift_k = q[3]; p.ssm_k = q[4]; p.ssm_D = q[5];
    p.a_re = q[7]; p.a_im = q[8]; p.b_re = q[9]; p.b_im = q[10]; p.c_re = q[11]; p.c_im = q[12]; p.log_dt = q[13]; p.dskip = q[14];
    p.out = (__nv_bfloat16*)d_out;
    fused_kernel<<<112, 384, SMEM_BYTES, st>>>(p);
    cudaLaunchConfig_t cfg = {};
    cfg.gridDim = dim3(NHELP); cfg.blockDim = dim3(128 * HELP_WG); cfg.dynamicSmemBytes = HELP_SMEM; cfg.stream = st;
    cudaLaunchAttribute at[1];
    at[0].id = cudaLaunchAttributeProgrammaticStreamSerialization; at[0].val.programmaticStreamSerializationAllowed = 1;
    cfg.attrs = at; cfg.numAttrs = 1;
    cudaLaunchKernelEx(&cfg, helper_kernel, p);
}

extern "C" void kernel_launch(void* const* d_in, const int* in_sizes, int n_in, void* d_out, int out_size) {
    launch_on(d_in, d_out, cudaStreamPerThread);
}
```

```cpp
#include <cuda_runtime.h>
#include <cuda_bf16.h>
#include <cuda.h>
#include <stdint.h>

namespace {

constexpr int XS = 4368;
constexpr int KS = 8320;
constexpr int PS = 4224;
constexpr int TBL = 28672;
constexpr int TBZ = TBL + 1344;
constexpr int O_PART = 2 * KS;
constexpr int O_KA = O_PART + 4 * PS;
constexpr int WGR = O_KA + 2 * KS;
constexpr int RAWB = 16640;
constexpr int O_YB = 0;
constexpr int O_YA = 16768;
constexpr int O_RV = 33536;
constexpr int O_RQ = 50176;
constexpr int O_XB = 66816;
constexpr int O_XA = O_XB + 4 * XS;
constexpr int O_WG = O_XA + 4 * XS + 128;
constexpr int O_PT = O_WG + 2 * WGR;
constexpr int O_BAR = O_PT + TBZ;
constexpr int SMEM_BYTES = O_BAR + 128;
static_assert(TBZ <= O_KA && SMEM_BYTES <= 232448, "smem");
enum { B_U = 0, B_KV = 8, B_YB2 = 16, B_YB3 = 24, B_S0 = 32, B_S1 = 40, B_XB0 = 48, B_XB1 = 56, B_XA = 64, B_YB1 = 72, B_YA = 80, B_Q = 88, B_KA0 = 96, B_KA1 = 104, B_K2 = 112, B_K3 = 120 };
#define HELP_POLLS 24
#define ORDER 0
#define T_U 600
#define T_K 1400
constexpr int NHELP = 20;
constexpr int HELP_WG = 6;
constexpr int HELP_SMEM = HELP_WG * TBL + 512;

__device__ uint4 g_pkt[112 * 128];
__device__ unsigned g_cnt[224];

struct Params {
    const __nv_bfloat16 *a_re, *a_im, *b_re, *b_im, *c_re, *c_im, *log_dt, *dskip, *shift_k, *ssm_k, *ssm_D;
    __nv_bfloat16* out;
};
struct Maps { CUtensorMap mu, mk, mv, mq; };

#define STAMP(role, i)
#define XST(a, i)
#define KSTAMP(i)
#define TSARG
#define TSPASS
#define TSINIT(addr, off)
#define TSFLUSH(blk)

__device__ __forceinline__ uint32_t lds32(uint32_t a) { uint32_t v; asm volatile("ld.shared.u32 %0, [%1];" : "=r"(v) : "r"(a)); return v; }
__device__ __forceinline__ uint32_t lds16(uint32_t a) { uint16_t v; asm volatile("ld.shared.u16 %0, [%1];" : "=h"(v) : "r"(a)); return v; }
__device__ __forceinline__ uint2 lds64(uint32_t a) { uint2 v; asm volatile("ld.shared.v2.u32 {%0,%1}, [%2];" : "=r"(v.x), "=r"(v.y) : "r"(a)); return v; }
__device__ __forceinline__ uint4 lds128(uint32_t a) { uint4 v; asm volatile("ld.shared.v4.u32 {%0,%1,%2,%3}, [%4];" : "=r"(v.x), "=r"(v.y), "=r"(v.z), "=r"(v.w) : "r"(a)); return v; }
__device__ __forceinline__ void sts16(uint32_t a, uint32_t v) { asm volatile("st.shared.u16 [%0], %1;" ::"r"(a), "h"((uint16_t)v) : "memory"); }
__device__ __forceinline__ void sts32(uint32_t a, uint32_t v) { asm volatile("st.shared.u32 [%0], %1;" ::"r"(a), "r"(v) : "memory"); }
__device__ __forceinline__ void sts64(uint32_t a, uint32_t x, uint32_t y) { asm volatile("st.shared.v2.u32 [%0], {%1,%2};" ::"r"(a), "r"(x), "r"(y) : "memory"); }
__device__ __forceinline__ void sts128(uint32_t a, uint32_t x, uint32_t y, uint32_t z, uint32_t w) { asm volatile("st.shared.v4.u32 [%0], {%1,%2,%3,%4};" ::"r"(a), "r"(x), "r"(y), "r"(z), "r"(w) : "memory"); }
__device__ __forceinline__ uint32_t ldg16(const void* p) { uint16_t v; asm volatile("ld.global.nc.u16 %0, [%1];" : "=h"(v) : "l"(p)); return v; }
__device__ __forceinline__ uint32_t ldg32(const void* p) { uint32_t v; asm volatile("ld.global.nc.u32 %0, [%1];" : "=r"(v) : "l"(p)); return v; }
__device__ __forceinline__ uint2 ldg64(const void* p) { uint2 v; asm volatile("ld.global.nc.v2.u32 {%0,%1}, [%2];" : "=r"(v.x), "=r"(v.y) : "l"(p)); return v; }
__device__ __forceinline__ uint4 ldg128(const void* p) { uint4 v; asm volatile("ld.global.nc.v4.u32 {%0,%1,%2,%3}, [%4];" : "=r"(v.x), "=r"(v.y), "=r"(v.z), "=r"(v.w) : "l"(p)); return v; }
__device__ __forceinline__ uint32_t pack(float lo, float hi) { uint32_t r; asm("cvt.rn.bf16x2.f32 %0, %1, %2;" : "=r"(r) : "f"(hi), "f"(lo)); return r; }
__device__ __forceinline__ uint32_t hadd(uint32_t a, uint32_t b) { uint32_t r; asm("add.rn.bf16x2 %0, %1, %2;" : "=r"(r) : "r"(a), "r"(b)); return r; }
__device__ __forceinline__ uint32_t hmul(uint32_t a, uint32_t b) { uint32_t r; asm("mul.rn.bf16x2 %0, %1, %2;" : "=r"(r) : "r"(a), "r"(b)); return r; }
__device__ __forceinline__ uint32_t hfma(uint32_t a, uint32_t b, uint32_t c) { uint32_t r; asm("fma.rn.bf16x2 %0, %1, %2, %3;" : "=r"(r) : "r"(a), "r"(b), "r"(c)); return r; }
__device__ __forceinline__ uint32_t hneg(uint32_t a) { uint32_t r; asm("neg.bf16x2 %0, %1;" : "=r"(r) : "r"(a)); return r; }
__device__ __forceinline__ uint32_t prmt(uint32_t a, uint32_t b, uint32_t s) { uint32_t r; asm("prmt.b32 %0, %1, %2, %3;" : "=r"(r) : "r"(a), "r"(b), "r"(s)); return r; }
__device__ __forceinline__ float blo(uint32_t v) { return __uint_as_float(v << 16); }
__device__ __forceinline__ float bhi(uint32_t v) { return __uint_as_float(v & 0xffff0000u); }
__device__ __forceinline__ uint32_t mapa(uint32_t a, uint32_t r) { uint32_t o; asm("mapa.shared::cluster.u32 %0, %1, %2;" : "=r"(o) : "r"(a), "r"(r)); return o; }
__device__ __forceinline__ void st_async(uint32_t a, uint32_t x, uint32_t y, uint32_t z, uint32_t w, uint32_t bar) {
    asm volatile("st.async.weak.shared::cluster.mbarrier::complete_tx::bytes.v4.b32 [%0], {%1,%2,%3,%4}, [%5];" ::"r"(a), "r"(x), "r"(y), "r"(z), "r"(w), "r"(bar) : "memory");
}
__device__ __forceinline__ void wait_bar(uint32_t bar) {
    uint32_t done = 0;
    for (int it = 0; it < (1 << 22); it++) {
        asm volatile("{ .reg .pred p; mbarrier.try_wait.parity.acquire.cluster.shared::cta.b64 p, [%1], 0; selp.u32 %0, 1, 0, p; }" : "=r"(done) : "r"(bar) : "memory");
        if (done) break;
    }
}
__device__ __forceinline__ void bar_sync(int id, int n) { asm volatile("bar.sync %0, %1;" ::"r"(id), "r"(n) : "memory"); }
__device__ __forceinline__ bool bar_and(int id, bool v) {
    uint32_t r;
    asm volatile("{ .reg .pred p, q; setp.ne.u32 p, %2, 0; barrier.cta.red.and.aligned.pred q, %1, 128, p; selp.u32 %0, 1, 0, q; }" : "=r"(r) : "r"(id), "r"((uint32_t)v) : "memory");
    return r;
}
__device__ __forceinline__ void bar_arrive(int id, int n) { asm volatile("bar.arrive %0, %1;" ::"r"(id), "r"(n) : "memory"); }
__device__ __forceinline__ void tma3d(uint32_t dst, const CUtensorMap* m, int c0, int c1, uint32_t bar) {
    asm volatile("cp.async.bulk.tensor.3d.shared::cluster.global.mbarrier::complete_tx::bytes [%0], [%1, {%3, %4, %5}], [%2];" ::"r"(dst), "l"(m), "r"(bar), "r"(c0), "r"(c1), "r"(0) : "memory");
}

template <int OFF, int SC>
__device__ __forceinline__ void wgmma32(float (&d)[128], uint32_t a0, uint32_t a1, uint32_t a2, uint32_t a3, uint32_t dlo) {
    if constexpr (SC == 0)
    asm volatile("{ .reg .b64 dsc; mov.b64 dsc, {%20, 8};\n wgmma.mma_async.sync.aligned.m64n32k16.f32.bf16.bf16 {%0, %1, %2, %3, %4, %5, %6, %7, %8, %9, %10, %11, %12, %13, %14, %15}, {%16, %17, %18, %19}, dsc, 0, 1, 1, 0; }"
                 : "=f"(d[OFF + 0]), "=f"(d[OFF + 1]), "=f"(d[OFF + 2]), "=f"(d[OFF + 3]), "=f"(d[OFF + 4]), "=f"(d[OFF + 5]), "=f"(d[OFF + 6]), "=f"(d[OFF + 7]), "=f"(d[OFF + 8]), "=f"(d[OFF + 9]), "=f"(d[OFF + 10]), "=f"(d[OFF + 11]), "=f"(d[OFF + 12]), "=f"(d[OFF + 13]), "=f"(d[OFF + 14]), "=f"(d[OFF + 15])
                 : "r"(a0), "r"(a1), "r"(a2), "r"(a3), "r"(dlo));
    else
    asm volatile("{ .reg .b64 dsc; mov.b64 dsc, {%20, 8};\n wgmma.mma_async.sync.aligned.m64n32k16.f32.bf16.bf16 {%0, %1, %2, %3, %4, %5, %6, %7, %8, %9, %10, %11, %12, %13, %14, %15}, {%16, %17, %18, %19}, dsc, %21, 1, 1, 0; }"
                 : "+f"(d[OFF + 0]), "+f"(d[OFF + 1]), "+f"(d[OFF + 2]), "+f"(d[OFF + 3]), "+f"(d[OFF + 4]), "+f"(d[OFF + 5]), "+f"(d[OFF + 6]), "+f"(d[OFF + 7]), "+f"(d[OFF + 8]), "+f"(d[OFF + 9]), "+f"(d[OFF + 10]), "+f"(d[OFF + 11]), "+f"(d[OFF + 12]), "+f"(d[OFF + 13]), "+f"(d[OFF + 14]), "+f"(d[OFF + 15])
                 : "r"(a0), "r"(a1), "r"(a2), "r"(a3), "r"(dlo), "n"(SC));
}
#define WG_FENCE asm volatile("wgmma.fence.sync.aligned;" ::: "memory");
#define WG_COMMIT asm volatile("wgmma.commit_group.sync.aligned;" ::: "memory");
#define WG_WAIT(n) asm volatile("wgmma.wait_group.sync.aligned %0;" ::"n"(n) : "memory");

template <int J, int B, int NB>
__device__ __forceinline__ void step_ranges(float (&d)[128], uint32_t (&a)[32], uint32_t desc) {
    if constexpr (B < NB) {
        wgmma32<16 * B, J != 0>(d, a[4 * (J & 7)], a[4 * (J & 7) + 1], a[4 * (J & 7) + 2], a[4 * (J & 7) + 3], desc + (32 * B + 16 * J));
        step_ranges<J, B + 1, NB>(d, a, desc);
    }
}
template <int P>
__device__ __forceinline__ void group(float (&d)[128], uint32_t (&a)[32], uint32_t desc) {
    WG_FENCE
    step_ranges<2 * P, 0, 8 - P>(d, a, desc);
    step_ranges<2 * P + 1, 0, 8 - P>(d, a, desc);
    WG_COMMIT
}
template <int B>
__device__ __forceinline__ void epi(float (&d)[128], uint32_t& carry, uint32_t pw) {
    uint32_t r[4];
#pragma unroll
    for (int k = 3; k >= 0; k--) {
        const int i = 4 * B + k;
        r[k] = pack(d[4 * i], d[4 * i + 1]);
        if (i < 31) r[k] = hadd(r[k], carry);
        if (i > 0) carry = pack(d[4 * i + 2], d[4 * i + 3]);
    }
    asm volatile("stmatrix.sync.aligned.m8n8.x4.trans.shared.b16 [%0], {%1,%2,%3,%4};" ::"r"(pw - B * 512), "r"(r[0]), "r"(r[1]), "r"(r[2]), "r"(r[3]) : "memory");
}
template <int P>
__device__ __forceinline__ void loadA(uint32_t (&a)[32], uint32_t ax) {
#pragma unroll
    for (int j = 2 * P; j < 2 * P + 2; j++) {
        a[4 * (j & 7)] = lds32(ax + 256 * j);
        a[4 * (j & 7) + 1] = lds32(ax + 256 * j + 128);
        a[4 * (j & 7) + 2] = lds32(ax + 256 * j + 16);
        a[4 * (j & 7) + 3] = lds32(ax + 256 * j + 144);
    }
}
__device__ __forceinline__ void reduce_push(uint32_t pr, uint32_t dst, uint32_t bar) {
    uint4 p0 = lds128(pr), p1 = lds128(pr + PS), p2 = lds128(pr + 2 * PS), p3 = lds128(pr + 3 * PS);
    st_async(dst, hadd(hadd(p0.x, p1.x), hadd(p2.x, p3.x)), hadd(hadd(p0.y, p1.y), hadd(p2.y, p3.y)),
             hadd(hadd(p0.z, p1.z), hadd(p2.z, p3.z)), hadd(hadd(p0.w, p1.w), hadd(p2.w, p3.w)), bar);
}

struct C2 { uint32_t re, im; };
__device__ __forceinline__ C2 cmul(C2 a, uint32_t s) {
    C2 r;
    asm("{ .reg .b16 l, h; .reg .b32 sl, sh, t, u, v;\n mov.b32 {l, h}, %4; mov.b32 sl, {l, l}; mov.b32 sh, {h, h};\n"
        "mul.rn.bf16x2 t, %3, sh; mul.bf16x2 u, %2, sl; sub.bf16x2 %0, u, t;\n"
        "mul.rn.bf16x2 v, %3, sl; fma.rn.bf16x2 %1, %2, sh, v; }" : "=r"(r.re), "=r"(r.im) : "r"(a.re), "r"(a.im), "r"(s));
    return r;
}
__device__ __forceinline__ void csq(float& re, float& im) { float t = re + re; re = fmaf(re, re, -im * im); im = t * im; }
__device__ __forceinline__ float ex2(float x) { float r; asm("ex2.approx.ftz.f32 %0, %1;" : "=f"(r) : "f"(x)); return r; }
__device__ __forceinline__ void st2(uint32_t are, uint32_t aim, C2 a, C2 b, C2 c, C2 d) { sts128(are, a.re, b.re, c.re, d.re); sts128(aim, a.im, b.im, c.im, d.im); }
struct KParams { uint32_t p[6], ldt, dsk; };
__device__ __forceinline__ void kgen_load(KParams& k, const Params& prm, int ch, int tid) {
    const size_t po = (size_t)ch * 256 + tid * 2;
    k.ldt = ldg16(prm.log_dt + ch);
    k.p[0] = ldg32(prm.a_re + po); k.p[1] = ldg32(prm.a_im + po); k.p[2] = ldg32(prm.b_re + po);
    k.p[3] = ldg32(prm.b_im + po); k.p[4] = ldg32(prm.c_re + po); k.p[5] = ldg32(prm.c_im + po);
    k.dsk = ldg16(prm.dskip + ch);
}
template <int SC>
__device__ __forceinline__ void wgmma48(float (&d)[24], uint32_t da, uint32_t db) {
    if constexpr (SC == 0)
        asm volatile("{ .reg .b64 da, db; mov.b64 da, {%24, 128}; mov.b64 db, {%25, 128};\n wgmma.mma_async.sync.aligned.m64n48k16.f32.bf16.bf16 {%0,%1,%2,%3,%4,%5,%6,%7,%8,%9,%10,%11,%12,%13,%14,%15,%16,%17,%18,%19,%20,%21,%22,%23}, da, db, 0, 1, 1, 1, 1; }"
                     : "=f"(d[0]), "=f"(d[1]), "=f"(d[2]), "=f"(d[3]), "=f"(d[4]), "=f"(d[5]), "=f"(d[6]), "=f"(d[7]), "=f"(d[8]), "=f"(d[9]), "=f"(d[10]), "=f"(d[11]), "=f"(d[12]), "=f"(d[13]), "=f"(d[14]), "=f"(d[15]), "=f"(d[16]), "=f"(d[17]), "=f"(d[18]), "=f"(d[19]), "=f"(d[20]), "=f"(d[21]), "=f"(d[22]), "=f"(d[23]) : "r"(da), "r"(db));
    else
        asm volatile("{ .reg .b64 da, db; mov.b64 da, {%24, 128}; mov.b64 db, {%25, 128};\n wgmma.mma_async.sync.aligned.m64n48k16.f32.bf16.bf16 {%0,%1,%2,%3,%4,%5,%6,%7,%8,%9,%10,%11,%12,%13,%14,%15,%16,%17,%18,%19,%20,%21,%22,%23}, da, db, 1, 1, 1, 1, 1; }"
                     : "+f"(d[0]), "+f"(d[1]), "+f"(d[2]), "+f"(d[3]), "+f"(d[4]), "+f"(d[5]), "+f"(d[6]), "+f"(d[7]), "+f"(d[8]), "+f"(d[9]), "+f"(d[10]), "+f"(d[11]), "+f"(d[12]), "+f"(d[13]), "+f"(d[14]), "+f"(d[15]), "+f"(d[16]), "+f"(d[17]), "+f"(d[18]), "+f"(d[19]), "+f"(d[20]), "+f"(d[21]), "+f"(d[22]), "+f"(d[23]) : "r"(da), "r"(db));
}
__device__ __forceinline__ void wait48(float (&d)[24]) {
    asm volatile("wgmma.wait_group.sync.aligned 0;" : "+f"(d[0]), "+f"(d[1]), "+f"(d[2]), "+f"(d[3]), "+f"(d[4]), "+f"(d[5]), "+f"(d[6]), "+f"(d[7]), "+f"(d[8]), "+f"(d[9]), "+f"(d[10]), "+f"(d[11]), "+f"(d[12]), "+f"(d[13]), "+f"(d[14]), "+f"(d[15]), "+f"(d[16]), "+f"(d[17]), "+f"(d[18]), "+f"(d[19]), "+f"(d[20]), "+f"(d[21]), "+f"(d[22]), "+f"(d[23]) :: "memory");
}
__device__ __forceinline__ void kext(float (&v)[6], const float (&d)[24]) {
    v[0] = d[0] - d[14]; v[1] = d[1] - d[15]; v[2] = d[4] - d[18]; v[3] = d[5] - d[19]; v[4] = d[8] - d[22]; v[5] = d[9] - d[23];
}
template <int PDB, bool EXT>
__device__ __forceinline__ void kgen_batch(const KParams& k, int b, uint32_t gb, int tid, int barid, float (&d)[24], float (&v)[6] TSARG) {
    const float dt = __bfloat162float(__float2bfloat16_rn(expf(blo(k.ldt))));
    const float dl = dt * 1.4426950408889634f;
    const uint32_t tb = gb + tid * 16, tp = tb + b * PDB;
    const uint32_t dsc = ((gb & 0x3FFFF) >> 4) | 0x80000, dsp = dsc + b * (PDB / 16);
    const uint32_t sel = b ? 0x3244 : 0x1044;
    const float al = __uint_as_float(prmt(k.p[0], 0, sel)) * dl, om = __uint_as_float(prmt(k.p[1], 0, sel)) * dt;
    const float br = __uint_as_float(prmt(k.p[2], 0, sel)) * dt, bi = __uint_as_float(prmt(k.p[3], 0, sel)) * dt;
    const float cr = __uint_as_float(prmt(k.p[4], 0, sel)), ci = __uint_as_float(prmt(k.p[5], 0, sel));
    const float wr = fmaf(cr, br, -ci * bi), wi = fmaf(cr, bi, ci * br);
    const float r1 = ex2(al), r64 = ex2(al * 64.f);
    float re = r1 * __cosf(om), im = r1 * __sinf(om);
    float hr = r64 * __cosf(om * 64.f), hi = r64 * __sinf(om * 64.f);
    const uint32_t s1 = pack(re, im);
    csq(re, im);
    const uint32_t s2 = pack(re, im);
    csq(re, im);
    C2 qa; qa.re = pack(wr, fmaf(wr, re, -wi * im)); qa.im = pack(wi, fmaf(wr, im, wi * re));
    csq(re, im);
    C2 p0; p0.re = pack(1.f, re); p0.im = pack(0.f, im);
    csq(re, im);
    const uint32_t s16 = pack(re, im);
    csq(re, im);
    const uint32_t s32 = pack(re, im);
    const uint32_t s64 = pack(hr, hi);
    csq(hr, hi);
    const uint32_t s128 = pack(hr, hi);
    csq(hr, hi);
    const uint32_t s256 = pack(hr, hi);
    csq(hr, hi);
    const uint32_t s512 = pack(hr, hi);
    csq(hr, hi);
    const uint32_t s1024 = pack(hr, hi);
    if (PDB == 0) { if (EXT) { wait48(d); kext(v, d); } bar_sync(barid, 128); }
    const C2 p1 = cmul(p0, s16), p2 = cmul(p0, s32), p3 = cmul(p1, s32);
    st2(tp, tp + 2048, p0, p1, p2, p3);
    st2(tp + 8192, tp + 10240, cmul(p0, s128), cmul(p1, s128), cmul(p2, s128), cmul(p3, s128));
    const C2 p4 = cmul(p0, s64), p5 = cmul(p1, s64), p6 = cmul(p2, s64), p7 = cmul(p3, s64);
    st2(tp + 4096, tp + 6144, p4, p5, p6, p7);
    st2(tp + 12288, tp + 14336, cmul(p4, s128), cmul(p5, s128), cmul(p6, s128), cmul(p7, s128));
    if (PDB != 0) { if (EXT) { wait48(d); kext(v, d); } bar_sync(barid, 128); }
    KSTAMP(17 + 3 * b);
    const C2 qb = cmul(qa, s2), qg = cmul(qa, s512);
    st2(tb + 16384, tb + 22528, qa, qb, cmul(qa, s1), cmul(qb, s1));
    st2(tb + 18432, tb + 24576, cmul(qa, s256), cmul(qb, s256), qg, cmul(qg, s256));
    C2 qf; qf.re = prmt(qa.re, qg.re, 0x5410); qf.im = prmt(qa.im, qg.im, 0x5410);
    const C2 qh = cmul(qf, s1024), qi = cmul(qh, s1024);
    st2(tb + 20480, tb + 26624, qh, cmul(qh, s256), qi, qi);
    asm volatile("fence.proxy.async.shared::cta;" ::: "memory");
    bar_sync(barid, 128);
    KSTAMP(18 + 3 * b);
    WG_FENCE
    wgmma48<0>(d, dsp, dsc + 1024);
#pragma unroll
    for (int s = 1; s < 8; s++) wgmma48<1>(d, dsp + 16 * s, dsc + 1024 + 16 * s);
    WG_COMMIT
}
__device__ __forceinline__ void kgen_end(const KParams& k, int tid, const float (&d)[24], const float (&v)[6], uint32_t (&o)[3]) {
    float u[6];
    kext(u, d);
    if (tid == 0) u[0] += blo(k.dsk);
    o[0] = pack(u[0] + v[0], u[1] + v[1]); o[1] = pack(u[2] + v[2], u[3] + v[3]); o[2] = pack(u[4] + v[4], u[5] + v[5]);
}
template <int PDB>
__device__ __forceinline__ void kgen(const KParams& k, uint32_t gb, int tid, int barid, uint32_t (&o)[3] TSARG) {
    float d[24], v[6];
#pragma unroll
    for (int i = 0; i < 24; i++) asm volatile("" : "=f"(d[i]));
#pragma unroll 1
    for (int b = 0; b < 2; b++) kgen_batch<PDB, true>(k, b, gb, tid, barid, d, v TSPASS);
    wait48(d);
    kgen_end(k, tid, d, v, o);
    KSTAMP(22);
}
__device__ __forceinline__ void kexpand(const uint32_t (&o)[3], uint32_t zb, uint32_t ke, int w, int lane, int barid TSARG) {
    {
        const int t = lane & 3, b = 8 * w + (lane >> 2);
        const uint32_t z0 = zb + 16 * b + 4 * (t & 1) + (t & 2);
        const uint32_t z1 = zb + (t < 2 ? 512 + 8 * b + 2 * t : 512 + 128 * t + 4 * b);
        const uint32_t z2 = zb + 1024 + (t == 2 ? 256 : 64 * t) + 2 * b;
        sts16(z0, o[0]); sts16(z0 + 8, o[0] >> 16);
        sts16(z1, o[1]); sts16(z1 + (t < 2 ? 4 : 2), o[1] >> 16);
        if (t < 3) sts16(z2, o[2]);
        if (t < 2) sts16(z2 + 128, o[2] >> 16);
    }
    if (barid < 3) KSTAMP(11);
    bar_sync(barid, 128);
    if (barid < 3) KSTAMP(12);
    uint32_t e0, e1, e2, e3, o0, o1, o2, o3;
    const uint32_t zc = zb + 1024 + (w * 32 + lane) * 2;
    const uint32_t v0 = lds16(zc), v1 = lds16(zc + 2);
    if (w & 2) {
        const uint32_t za = zb + 768 + ((w - 2) * 32 + lane) * 4;
        const uint32_t v = lds32(za), v2 = lds32(za + 4);
        e0 = prmt(v, 0, 0x1010); e1 = v; e2 = prmt(v, 0, 0x3232); e3 = prmt(v2, 0, 0x1010);
        o0 = e0; o1 = e0; o2 = e2; o3 = prmt(v, v2, 0x5432);
    } else if (w & 1) {
        const uint2 v = lds64(zb + 512 + lane * 8);
        const uint32_t v4 = lds32(zb + 512 + lane * 8 + 8), pv = lds32(zb + 508);
        e0 = prmt(v.x, 0, 0x1010); e1 = prmt(v.x, v.y, 0x5432); e2 = prmt(v.y, 0, 0x1010); e3 = prmt(v.y, v4, 0x5432);
        o0 = lane ? e0 : prmt(pv, v.x, 0x5432); o1 = v.x; o2 = e2; o3 = v.y;
    } else {
        const uint4 e = lds128(zb + lane * 16);
        uint32_t p = lds32(zb + lane * 16 - 4);
        if (lane == 0) p = 0;
        e0 = e.x; e1 = e.y; e2 = e.z; e3 = e.w;
        o0 = prmt(p, e.x, 0x5432); o1 = prmt(e.x, e.y, 0x5432); o2 = prmt(e.y, e.z, 0x5432); o3 = prmt(e.z, e.w, 0x5432);
    }
    if (w == 3 && lane < 2) sts128(ke + lane * 4160, 0, 0, 0, 0);
    ke += 16 + w * 512 + lane * 16;
    sts128(ke, e0, e1, e2, e3);
    sts128(ke + 4160, o0, o1, o2, o3);
    const uint32_t d0 = v0 * 0x10001u, d1 = v1 * 0x10001u, m = v0 | (v1 << 16);
    sts128(ke + 2048, d0, d0, (lane & 1) ? d1 : m, d1);
    sts128(ke + 2048 + 4160, d0, d0, (lane & 1) ? m : d0, d1);
}

template <bool GATE>
__device__ __forceinline__ void final_pass(uint32_t ybase, uint32_t qbase, __nv_bfloat16* outp, int i0, int i1, int lane) {
    const int r = lane & 7, k = lane >> 3, g = lane >> 2, t = lane & 3;
    const int ch = 8 * ((r >> 1) & 1) + 2 * k + (r & 1);
    const uint32_t ya = ybase + ch * 1040 + (ch >> 3) * 64 + (r >> 2) * 32;
    const uint32_t qa = qbase + g * 2080 + (2 * (t >> 1) + 1) * 32 + (t & 1) * 16;
    char* op = (char*)outp + (size_t)(16 * (t >> 1) + g) * 1792 + (t & 1) * 16;
#pragma unroll 2
    for (int i = i0; i < i1; i += 4) {
        const int c = (i & 1) + 4 * (i >> 1);
        uint32_t v0, v1, v2, v3;
        asm volatile("ldmatrix.sync.aligned.m8n8.x4.trans.shared.b16 {%0,%1,%2,%3}, [%4];" : "=r"(v0), "=r"(v1), "=r"(v2), "=r"(v3) : "r"(ya + c * 16));
        if (GATE) {
            uint4 q = lds128(qa + c * 32);
            v0 = hmul(v0, q.x); v1 = hmul(v1, q.y); v2 = hmul(v2, q.z); v3 = hmul(v3, q.w);
        }
        asm volatile("st.global.v4.b32 [%0], {%1,%2,%3,%4};" ::"l"(op + (size_t)c * (8 * 1792)), "r"(v0), "r"(v1), "r"(v2), "r"(v3) : "memory");
    }
}

__device__ __forceinline__ void push4(uint32_t dd, const uint32_t (&R)[8], uint32_t bx) {
    st_async(dd, prmt(R[7], R[6], 0x5410), prmt(R[5], R[4], 0x5410), prmt(R[3], R[2], 0x5410), prmt(R[1], R[0], 0x5410), bx);
    st_async(dd + XS, prmt(R[7], R[6], 0x7632), prmt(R[5], R[4], 0x7632), prmt(R[3], R[2], 0x7632), prmt(R[1], R[0], 0x7632), bx);
}
__device__ __forceinline__ void expect_tx(uint32_t bar, uint32_t n) { asm volatile("mbarrier.arrive.expect_tx.shared.b64 _, [%0], %1;" ::"r"(bar), "r"(n) : "memory"); }
__device__ __forceinline__ void bulk_g2s(uint32_t dst, const void* src, uint32_t n, uint32_t bar) {
    asm volatile("cp.async.bulk.shared::cluster.global.mbarrier::complete_tx::bytes [%0], [%1], %2, [%3];" ::"r"(dst), "l"(src), "r"(n), "r"(bar) : "memory");
}

__device__ __forceinline__ void warp_arrive(uint32_t bar, int lane) {
    __syncwarp();
    if (lane == 0) asm volatile("mbarrier.arrive.shared.b64 _, [%0];" ::"r"(bar) : "memory");
}

__global__ void __cluster_dims__(4, 1, 1) __launch_bounds__(384, 1) fused_kernel(const __grid_constant__ Params prm, const __grid_constant__ Maps mp) {
    extern __shared__ __align__(1024) char smem[];
    asm volatile("griddepcontrol.launch_dependents;");
    const uint32_t base = (uint32_t)__cvta_generic_to_shared(smem);
    const uint32_t bars = base + O_BAR;
    const int wg = __shfl_sync(0xffffffff, threadIdx.x >> 7, 0);
    const int tid = threadIdx.x & 127, lane = threadIdx.x & 31;
    const int w = __shfl_sync(0xffffffff, tid >> 5, 0);
    const int rank = blockIdx.x & 3, cl = blockIdx.x >> 2;
    const int ch0 = 4 * blockIdx.x;
    TSINIT(base + (wg == 0 ? O_YB + 16688 : wg == 1 ? O_YA + 16688 : O_YB + 16736), wg == 2 ? O_YA - 32 : 0)
    const unsigned t0 = clock();
    if (wg == 2) {
        if (lane == 0) {
            const uint32_t bw = bars + 32 * w, cnt = w == 3 ? 4 : 1;
#pragma unroll
            for (int i = 0; i < 4; i++) asm volatile("mbarrier.init.shared.b64 [%0], %1;" ::"r"(bw + 8 * i), "r"(cnt) : "memory");
            asm volatile("fence.mbarrier_init.release.cluster;" ::: "memory");
            asm volatile("fence.proxy.async.shared::cta;" ::: "memory");
            if (w < 3) {
                expect_tx(bw, w ? 8192 * w : RAWB);
                expect_tx(bw + 8, w ? 8192 : 2 * RAWB);
                expect_tx(bw + 16, w ? 8192 * w : 6144);
                expect_tx(bw + 24, w == 0 ? 2048 : w == 2 ? RAWB : 8192);
            }
        }
        __syncwarp();
    }
    asm volatile("barrier.cluster.arrive.relaxed.aligned;" ::: "memory");
    if (wg == 2 && w == 1 && lane < 28) {
        if (lane < 24) asm volatile("prefetch.global.L2 [%0];" ::"l"((&prm.a_re)[lane >> 2] + (ch0 + 3) * 256 + (lane & 3) * 64) : "memory");
        else asm volatile("prefetch.tensormap [%0];" ::"l"(&mp.mu + (lane - 24)) : "memory");
    }
    if (wg == 2) {
        asm volatile("setmaxnreg.dec.sync.aligned.u32 104;");
        const int c4 = tid & 3, gam = tid >> 2;
        const uint4 s0 = ldg128(prm.shift_k + (16 * cl + 4 * c4) * 4), s1 = ldg128(prm.shift_k + (16 * cl + 4 * c4) * 4 + 8);
        const uint32_t dA = ldg32(prm.ssm_D + ch0 + (w & 2));
        if (tid == 0) {
            while ((unsigned)clock() - t0 < T_U) {}
            tma3d(base + O_YB, &mp.mu, 16 * cl, 64 * rank - 1, bars + B_U);
            while ((unsigned)clock() - t0 < T_K) {}
            tma3d(base + O_YA, &mp.mk, 16 * cl, 64 * rank - 1, bars + B_KV);
            tma3d(base + O_RV, &mp.mv, 16 * cl, 64 * rank - 1, bars + B_KV);
        }
        __syncwarp();
        asm volatile("barrier.cluster.wait.acquire.aligned;" ::: "memory");
        STAMP(2, 0);
        const uint32_t roff = (gam + 1) * 32 + c4 * 8;
        const uint32_t xdst = mapa(base + 32 * c4 + 16 * (255 - 64 * rank - gam), c4);
        wait_bar(bars + B_U);
        STAMP(2, 1);
        if (lane == 0) bulk_g2s(base + O_WG + (w & 1) * WGR + O_KA + (w >> 1) * KS + 16, prm.ssm_k + (size_t)(ch0 + 2 * (w & 1) + (w >> 1)) * 2048, 4096, bars + B_S0 + 8 * (w >> 1));
        __syncwarp();
        {
            uint32_t Rx[2][8], Ry[2][8];
#pragma unroll
            for (int pass = 0; pass < 2; pass++)
#pragma unroll
                for (int i = 0; i < 8; i++) { uint2 v = lds64(base + O_YB + roff + pass * 1024 + i * 2080); Rx[pass][i] = v.x; Ry[pass][i] = v.y; }
            const uint32_t bx = mapa(bars + B_XB0, c4);
            push4(xdst + O_XB, Rx[0], bx);
            push4(xdst + O_XB - 512, Rx[1], bx);
            push4(xdst + O_XB + 2 * XS, Ry[0], bx + 8);
            push4(xdst + O_XB + 2 * XS - 512, Ry[1], bx + 8);
        }
        STAMP(2, 2);
        KParams kp;
        kgen_load(kp, prm, ch0 + 2, tid);
        {
            uint32_t W[4][2];
            W[0][0] = prmt(s0.x, s0.z, 0x5410); W[1][0] = prmt(s0.x, s0.z, 0x7632); W[2][0] = prmt(s0.y, s0.w, 0x5410); W[3][0] = prmt(s0.y, s0.w, 0x7632);
            W[0][1] = prmt(s1.x, s1.z, 0x5410); W[1][1] = prmt(s1.x, s1.z, 0x7632); W[2][1] = prmt(s1.y, s1.w, 0x5410); W[3][1] = prmt(s1.y, s1.w, 0x7632);
            wait_bar(bars + B_KV);
            STAMP(2, 4);
            if (tid == 0) tma3d(base + O_RQ, &mp.mq, 16 * cl, 64 * rank - 1, bars + B_Q);
            __syncwarp();
            const uint32_t bx = mapa(bars + B_XA, c4);
#pragma unroll 1
            for (int pass = 0; pass < 2; pass++) {
                const uint32_t kb = base + O_YA + roff + pass * 1024, vb = base + O_RV + roff + pass * 1024;
                uint2 k3 = lds64(kb - 32 + 5 * 2080), k2 = lds64(kb - 32 + 6 * 2080), k1 = lds64(kb - 32 + 7 * 2080);
                uint32_t Rx[8], Ry[8];
#pragma unroll
                for (int i = 0; i < 8; i++) {
                    uint2 k0 = lds64(kb + i * 2080), v = lds64(vb + i * 2080);
                    Rx[i] = hmul(hfma(k0.x, W[0][0], hfma(k1.x, W[1][0], hfma(k2.x, W[2][0], hmul(k3.x, W[3][0])))), v.x);
                    Ry[i] = hmul(hfma(k0.y, W[0][1], hfma(k1.y, W[1][1], hfma(k2.y, W[2][1], hmul(k3.y, W[3][1])))), v.y);
                    k3 = k2; k2 = k1; k1 = k0;
                }
                push4(xdst + O_XA - pass * 512, Rx, bx);
                push4(xdst + O_XA + 2 * XS - pass * 512, Ry, bx);
            }
        }
        STAMP(2, 5);
        unsigned tag = *(volatile unsigned*)&g_cnt[blockIdx.x];
#pragma unroll 1
        for (int st = 0; st < 2; st++) {
            const uint32_t ka = base + O_WG + (w >> 1) * WGR + O_KA + st * KS + 16 + (w & 1) * 2048 + lane * 16;
            wait_bar(bars + B_S0 + 8 * st);
            uint4 e[4];
            uint32_t p[4];
#pragma unroll
            for (int i = 0; i < 4; i++) { e[i] = lds128(ka + i * 512); p[i] = lds32(ka + i * 512 - 4); }
            if ((w & 1) == 0 && lane == 0) {
                e[0].x = (e[0].x & 0xffff0000u) | (pack(blo(e[0].x) + (st ? bhi(dA) : blo(dA)), 0.f) & 0xffffu);
                p[0] = 0;
                sts32(ka, e[0].x);
                sts128(ka - 16, 0, 0, 0, 0);
                sts128(ka - 16 + 4160, 0, 0, 0, 0);
            }
#pragma unroll
            for (int i = 0; i < 4; i++)
                sts128(ka + i * 512 + 4160, prmt(p[i], e[i].x, 0x5432), prmt(e[i].x, e[i].y, 0x5432), prmt(e[i].y, e[i].z, 0x5432), prmt(e[i].z, e[i].w, 0x5432));
            warp_arrive(bars + B_KA0 + 8 * st, lane);
            STAMP(2, 6 + st);
        }
        bar_sync(7, 384);
#pragma unroll 1
        for (int job = 0; job < 2; job++) {
            uint32_t o[3];
            bool local = true;
            if (job) {
                tag++;
                if (tid == 0) g_cnt[blockIdx.x] = tag;
                bool ok = false;
#pragma unroll 1
                for (int it = 0; it < HELP_POLLS && !ok; it++) {
                    uint32_t tg;
                    asm volatile("{ .reg .b128 v; .reg .b64 l, h; ld.relaxed.gpu.global.b128 v, [%4]; mov.b128 {l, h}, v; mov.b64 {%0, %1}, l; mov.b64 {%2, %3}, h; }"
                                 : "=r"(o[0]), "=r"(o[1]), "=r"(o[2]), "=r"(tg) : "l"(g_pkt + blockIdx.x * 128 + tid) : "memory");
                    ok = tg == tag;
                }
                local = !bar_and(6, ok);
                if (local) kgen_load(kp, prm, ch0 + 3, tid);
                STAMP(2, 9);
            }
            if (local) {
                float v[6];
#pragma unroll 1
                for (int b = 0; b < 2; b++) {
                    float d[24];
                    kgen_batch<0, false>(kp, b, base + O_PT, tid, 6, d, v TSPASS);
                    wait48(d);
                    if (b) { kgen_end(kp, tid, d, v, o); break; }
                    kext(v, d);
                    STAMP(2, 3);
                }
            }
            kexpand(o, base + O_PT + TBL, base + O_WG + job * WGR + KS, w, lane, 6 TSPASS);
            warp_arrive(bars + B_K2 + 8 * job, lane);
            STAMP(2, 8 + 2 * job);
        }
        wait_bar(bars + B_Q);
        wait_bar(bars + B_YA);
        STAMP(wg, 11);
        final_pass<true>(base + O_YA, base + O_RQ, prm.out + (size_t)(512 * rank) * 896 + 16 * cl, w, 32, lane);
        STAMP(wg, 12);
#pragma unroll 1
        for (int s = 0; s < 3; s++) {
            wait_bar(bars + (s ? B_YB2 - 8 + 8 * s : B_YB1));
            if (s == 2) STAMP(wg, 13);
            const int row0 = s == 0 ? 256 * rank : s == 1 ? 768 + 192 * rank : 1344 + 64 * rank;
            final_pass<false>(base + O_YB, 0, prm.out + (size_t)row0 * 896 + 448 + 16 * cl, w + (s ? 4 + 12 * s : 0), s == 0 ? 16 : 24 + 4 * s, lane);
        }
        STAMP(wg, 14);
    } else {
        KParams kp;
        kgen_load(kp, prm, ch0 + wg, tid);
        const int g = lane >> 2, t = lane & 3;
        const uint32_t wgb = base + O_WG + wg * WGR;
        const uint32_t xb = base + O_XB + 32 * rank;
        if (lane < 17) sts128(xb + (w < 2 ? wg + 2 * w : 2 + 2 * wg + w) * XS + 4096 + lane * 16, 0, 0, 0, 0);
        const uint32_t aoff = wgb + 16 + ((g & 1) ? 0 : 4160) + 4 * (8 * w + t + (g >> 1) - 3);
        const uint32_t pw = wgb + O_PART + w * PS + 16 * (255 + 2 * w - lane);
        const uint32_t pr = wgb + O_PART + tid * 16;
        const uint32_t yloc = base + (4 * rank * 1040 + (rank >> 1) * 64);
        const int r2 = w == 3 ? lane >> 3 : tid / 24;
        const uint32_t yA = mapa(yloc + O_YA + (tid & 63) * 16, w >> 1);
        const uint32_t yB0 = mapa(yloc + O_YB + lane * 16, w), yB1 = mapa(yloc + O_YB + (w == 3 ? 56 + (lane & 7) : 32 + tid - 24 * r2) * 16, r2);
        const uint32_t ystep = mapa(yloc, 2) - mapa(yloc, 0), bl = bars & 0xffffff;
        asm volatile("setmaxnreg.inc.sync.aligned.u32 200;");
        asm volatile("barrier.cluster.wait.acquire.aligned;" ::: "memory");
        STAMP(wg, 0);
        {
            uint32_t o[3];
            kgen<0>(kp, wgb, tid, 1 + wg, o TSPASS);
            bar_arrive(7, 384);
            kexpand(o, wgb + TBL, wgb, w, lane, 1 + wg TSPASS);
            KSTAMP(23);
        }
        wait_bar(bars + B_XB0);
        asm volatile("fence.proxy.async.shared::cta;" ::: "memory");
        bar_sync(1 + wg, 128);
        if (lane < 2 * w) sts128(wgb + O_PART + w * PS + lane * 16, 0, 0, 0, 0);
        STAMP(wg, 1);
        float d[128];
        uint32_t a[32];
        uint32_t carry = 0;
        bool pref = false;
        uint32_t y1 = 0, b1 = 0;
        uint32_t axc = aoff;
#pragma unroll 1
        for (int c = 0; c < 4; c++) {
            const bool isB = (c == 0) | (c == 3);
            const int chl = isB ? (c ? 2 + wg : wg) : c - 1 + 2 * wg;
            const uint32_t axn = aoff + (c == 2 ? KS : O_KA + c * KS);
            const uint32_t kbar = bars + B_KA0 + 8 * c + (c == 2 ? 8 * wg : 0);
            if (c & 1) {
                wait_bar(bars + (isB ? B_XB1 : B_XA));
                asm volatile("fence.proxy.async.shared::cta;" ::: "memory");
            }
            if (!pref) { loadA<0>(a, axc); loadA<1>(a, axc); loadA<2>(a, axc); loadA<3>(a, axc); }
            STAMP(wg, 2 + 2 * c);
            const uint32_t xa = xb + (isB ? chl : 4 + chl) * XS;
            const uint32_t desc = ((xa & 0x3FFFF) >> 4) | 0x10000;
            group<0>(d, a, desc);
            if (c) {
                bar_sync(1 + wg, 128);
                reduce_push(pr + 2048, y1, b1);
            }
            group<1>(d, a, desc);
            bar_sync(1 + wg, 128);
#define STAGE(P) WG_WAIT(1) epi<7 - P>(d, carry, pw);
            STAGE(0) loadA<4>(a, axc); group<2>(d, a, desc);
            STAGE(1) loadA<5>(a, axc); group<3>(d, a, desc);
            STAGE(2) loadA<6>(a, axc); group<4>(d, a, desc);
            STAGE(3) loadA<7>(a, axc); group<5>(d, a, desc);
            {
                const uint32_t y0 = (isB ? yB0 : yA) + chl * 1040;
                y1 = (isB ? yB1 : yA + ystep) + chl * 1040;
                b1 = (y1 & 0xff000000u) | (bl + (isB ? (w == 3 ? B_YB3 : B_YB2) : B_YA));
                bar_sync(1 + wg, 128);
                reduce_push(pr, y0, (y0 & 0xff000000u) | (bl + (isB ? B_YB1 : B_YA)));
                uint32_t done;
                asm volatile("{ .reg .pred p; mbarrier.test_wait.parity.shared::cta.b64 p, [%1], 0; selp.u32 %0, 1, 0, p; }" : "=r"(done) : "r"(kbar) : "memory");
                pref = __all_sync(0xffffffff, done) && c < 3;
            }
            STAGE(4) if (pref) loadA<0>(a, axn); group<6>(d, a, desc);
            STAGE(5) if (pref) loadA<1>(a, axn); group<7>(d, a, desc);
            STAGE(6) if (pref) loadA<2>(a, axn);
            if (c == 3) {
                bar_sync(1 + wg, 128);
                if (w < 3) reduce_push(pr + 2048, y1, b1);
            }
            WG_WAIT(0) epi<0>(d, carry, pw); if (pref) loadA<3>(a, axn);
            axc = axn;
            STAMP(wg, 3 + 2 * c);
            if (!pref && c < 3) wait_bar(kbar);
        }
        bar_sync(1 + wg, 128);
        if (w == 3) reduce_push(pr + 2048, y1, b1);
        STAMP(wg, 10);
    }
    TSFLUSH(blockIdx.x);
}

__global__ void __launch_bounds__(128 * HELP_WG, 1) helper_kernel(const __grid_constant__ Params prm) {
    extern __shared__ __align__(1024) char smem[];
    const uint32_t base = (uint32_t)__cvta_generic_to_shared(smem);
    const int grp = __shfl_sync(0xffffffff, threadIdx.x >> 7, 0);
    const int tid = threadIdx.x & 127;
    const int hi = grp * NHELP + blockIdx.x;
    TSINIT(base + HELP_WG * TBL + grp * 64, 0)
    KParams kp;
    if (hi < 112) {
        kgen_load(kp, prm, 4 * hi + 3, tid);
        unsigned tag = *(volatile unsigned*)&g_cnt[112 + hi];
        uint32_t o[3];
        kgen<0>(kp, base + grp * TBL, tid, 1 + grp, o TSPASS);
        tag++;
        if (tid == 0) g_cnt[112 + hi] = tag;
        asm volatile("{ .reg .b128 v; .reg .b64 l, h; mov.b64 l, {%0, %1}; mov.b64 h, {%2, %3}; mov.b128 v, {l, h}; st.relaxed.gpu.global.b128 [%4], v; }"
                     ::"r"(o[0]), "r"(o[1]), "r"(o[2]), "r"(tag), "l"(g_pkt + hi * 128 + tid) : "memory");
        STAMP(0, 23);
        TSFLUSH(112 + blockIdx.x);
    }
}

typedef CUresult (*EncodeFn)(CUtensorMap*, CUtensorMapDataType, cuuint32_t, void*, const cuuint64_t*, const cuuint64_t*, const cuuint32_t*, const cuuint32_t*,
                             CUtensorMapInterleave, CUtensorMapSwizzle, CUtensorMapL2promotion, CUtensorMapFloatOOBfill);

}

static void launch_on(void* const* d_in, void* d_out, cudaStream_t st) {
    static EncodeFn enc = nullptr;
    if (!enc) {
        cudaDriverEntryPointQueryResult qr;
        cudaGetDriverEntryPoint("cuTensorMapEncodeTiled", (void**)&enc, cudaEnableDefault, &qr);
        cudaFuncSetAttribute(fused_kernel, cudaFuncAttributeMaxDynamicSharedMemorySize, SMEM_BYTES);
        cudaFuncSetAttribute(helper_kernel, cudaFuncAttributeMaxDynamicSharedMemorySize, HELP_SMEM);
    }
    Params p;
    Maps mp;
    CUtensorMap* maps[4] = {&mp.mq, &mp.mk, &mp.mv, &mp.mu};
    void* ptrs[4] = {d_in[0], d_in[1], d_in[2], d_in[6]};
    for (int i = 0; i < 4; i++) {
        cuuint64_t gd[3] = {448, 256, 8}, gs[2] = {7168, 896};
        cuuint32_t bx[3] = {16, 65, 8}, es[3] = {1, 1, 1};
        enc(maps[i], CU_TENSOR_MAP_DATA_TYPE_BFLOAT16, 3, ptrs[i], gd, gs, bx, es, CU_TENSOR_MAP_INTERLEAVE_NONE, CU_TENSOR_MAP_SWIZZLE_NONE,
            CU_TENSOR_MAP_L2_PROMOTION_NONE, CU_TENSOR_MAP_FLOAT_OOB_FILL_NONE);
    }
    const __nv_bfloat16* const* q = (const __nv_bfloat16* const*)d_in;
    p.shift_k = q[3]; p.ssm_k = q[4]; p.ssm_D = q[5];
    p.a_re = q[7]; p.a_im = q[8]; p.b_re = q[9]; p.b_im = q[10]; p.c_re = q[11]; p.c_im = q[12]; p.log_dt = q[13]; p.dskip = q[14];
    p.out = (__nv_bfloat16*)d_out;
    fused_kernel<<<112, 384, SMEM_BYTES, st>>>(p, mp);
    cudaLaunchConfig_t cfg = {};
    cfg.gridDim = dim3(NHELP); cfg.blockDim = dim3(128 * HELP_WG); cfg.dynamicSmemBytes = HELP_SMEM; cfg.stream = st;
    cudaLaunchAttribute at[1];
    at[0].id = cudaLaunchAttributeProgrammaticStreamSerialization; at[0].val.programmaticStreamSerializationAllowed = 1;
    cfg.attrs = at; cfg.numAttrs = 1;
    cudaLaunchKernelEx(&cfg, helper_kernel, p);
}

extern "C" void kernel_launch(void* const* d_in, const int* in_sizes, int n_in, void* d_out, int out_size) {
    launch_on(d_in, d_out, cudaStreamPerThread);
}
```

```cpp
#include <cuda_runtime.h>
#include <cuda_bf16.h>
#include <cuda.h>
#include <stdint.h>

namespace {

constexpr int XS = 4368;
constexpr int KS = 8320;
constexpr int PS = 4224;
constexpr int TBL = 28672;
constexpr int TBZ = TBL + 1344;
constexpr int O_PART = 2 * KS;
constexpr int O_KA = O_PART + 4 * PS;
constexpr int WGR = O_KA + 2 * KS;
constexpr int RAWB = 16640;
constexpr int QB = 8448;
constexpr int O_YB = 0;
constexpr int O_YA = 16768;
constexpr int O_RV = 33536;
constexpr int O_RQ = 50176;
constexpr int O_XB = 66816;
constexpr int O_XA = O_XB + 4 * XS;
constexpr int O_WG = O_XA + 4 * XS + 128;
constexpr int O_PT = O_WG + 2 * WGR;
constexpr int O_BAR = O_PT + TBZ;
constexpr int SMEM_BYTES = O_BAR + 128;
static_assert(TBZ <= O_KA && SMEM_BYTES <= 232448, "smem");
enum { B_U = 0, B_KV = 8, B_S0 = 16, B_S1 = 24, B_YB2 = 32, B_YB3 = 40, B_XB0 = 48, B_XB1 = 56, B_XA = 64, B_YB1 = 72, B_YA1 = 80, B_YA2 = 88, B_KA0 = 96, B_KA1 = 104, B_K2 = 112, B_K3 = 120 };
#define HELP_POLLS 40
#define ORDER 0
#define T_U 600
#define T_K 1400
constexpr int NHELP = 20;
constexpr int HELP_WG = 6;
constexpr int HELP_SMEM = HELP_WG * TBL + 512;

__device__ uint4 g_pkt[112 * 128];
__device__ unsigned g_cnt[224];

struct Params {
    const __nv_bfloat16 *a_re, *a_im, *b_re, *b_im, *c_re, *c_im, *log_dt, *dskip, *shift_k, *ssm_k, *ssm_D;
    __nv_bfloat16* out;
};
struct Maps { CUtensorMap mu, mk, mv, mq; };

#define STAMP(role, i)
#define XST(a, i)
#define KSTAMP(i)
#define TSARG
#define TSPASS
#define TSINIT(addr, off)
#define TSFLUSH(blk)

__device__ __forceinline__ uint32_t lds32(uint32_t a) { uint32_t v; asm volatile("ld.shared.u32 %0, [%1];" : "=r"(v) : "r"(a)); return v; }
__device__ __forceinline__ uint32_t lds16(uint32_t a) { uint16_t v; asm volatile("ld.shared.u16 %0, [%1];" : "=h"(v) : "r"(a)); return v; }
__device__ __forceinline__ uint2 lds64(uint32_t a) { uint2 v; asm volatile("ld.shared.v2.u32 {%0,%1}, [%2];" : "=r"(v.x), "=r"(v.y) : "r"(a)); return v; }
__device__ __forceinline__ uint4 lds128(uint32_t a) { uint4 v; asm volatile("ld.shared.v4.u32 {%0,%1,%2,%3}, [%4];" : "=r"(v.x), "=r"(v.y), "=r"(v.z), "=r"(v.w) : "r"(a)); return v; }
__device__ __forceinline__ void sts16(uint32_t a, uint32_t v) { asm volatile("st.shared.u16 [%0], %1;" ::"r"(a), "h"((uint16_t)v) : "memory"); }
__device__ __forceinline__ void sts32(uint32_t a, uint32_t v) { asm volatile("st.shared.u32 [%0], %1;" ::"r"(a), "r"(v) : "memory"); }
__device__ __forceinline__ void sts64(uint32_t a, uint32_t x, uint32_t y) { asm volatile("st.shared.v2.u32 [%0], {%1,%2};" ::"r"(a), "r"(x), "r"(y) : "memory"); }
__device__ __forceinline__ void sts128(uint32_t a, uint32_t x, uint32_t y, uint32_t z, uint32_t w) { asm volatile("st.shared.v4.u32 [%0], {%1,%2,%3,%4};" ::"r"(a), "r"(x), "r"(y), "r"(z), "r"(w) : "memory"); }
__device__ __forceinline__ uint32_t ldg16(const void* p) { uint16_t v; asm volatile("ld.global.nc.u16 %0, [%1];" : "=h"(v) : "l"(p)); return v; }
__device__ __forceinline__ uint32_t ldg32(const void* p) { uint32_t v; asm volatile("ld.global.nc.u32 %0, [%1];" : "=r"(v) : "l"(p)); return v; }
__device__ __forceinline__ uint2 ldg64(const void* p) { uint2 v; asm volatile("ld.global.nc.v2.u32 {%0,%1}, [%2];" : "=r"(v.x), "=r"(v.y) : "l"(p)); return v; }
__device__ __forceinline__ uint4 ldg128(const void* p) { uint4 v; asm volatile("ld.global.nc.v4.u32 {%0,%1,%2,%3}, [%4];" : "=r"(v.x), "=r"(v.y), "=r"(v.z), "=r"(v.w) : "l"(p)); return v; }
__device__ __forceinline__ uint32_t pack(float lo, float hi) { uint32_t r; asm("cvt.rn.bf16x2.f32 %0, %1, %2;" : "=r"(r) : "f"(hi), "f"(lo)); return r; }
__device__ __forceinline__ uint32_t hadd(uint32_t a, uint32_t b) { uint32_t r; asm("add.rn.bf16x2 %0, %1, %2;" : "=r"(r) : "r"(a), "r"(b)); return r; }
__device__ __forceinline__ uint32_t hmul(uint32_t a, uint32_t b) { uint32_t r; asm("mul.rn.bf16x2 %0, %1, %2;" : "=r"(r) : "r"(a), "r"(b)); return r; }
__device__ __forceinline__ uint32_t hfma(uint32_t a, uint32_t b, uint32_t c) { uint32_t r; asm("fma.rn.bf16x2 %0, %1, %2, %3;" : "=r"(r) : "r"(a), "r"(b), "r"(c)); return r; }
__device__ __forceinline__ uint32_t hneg(uint32_t a) { uint32_t r; asm("neg.bf16x2 %0, %1;" : "=r"(r) : "r"(a)); return r; }
__device__ __forceinline__ uint32_t prmt(uint32_t a, uint32_t b, uint32_t s) { uint32_t r; asm("prmt.b32 %0, %1, %2, %3;" : "=r"(r) : "r"(a), "r"(b), "r"(s)); return r; }
__device__ __forceinline__ float blo(uint32_t v) { return __uint_as_float(v << 16); }
__device__ __forceinline__ float bhi(uint32_t v) { return __uint_as_float(v & 0xffff0000u); }
__device__ __forceinline__ uint32_t mapa(uint32_t a, uint32_t r) { uint32_t o; asm("mapa.shared::cluster.u32 %0, %1, %2;" : "=r"(o) : "r"(a), "r"(r)); return o; }
__device__ __forceinline__ void st_async(uint32_t a, uint32_t x, uint32_t y, uint32_t z, uint32_t w, uint32_t bar) {
    asm volatile("st.async.weak.shared::cluster.mbarrier::complete_tx::bytes.v4.b32 [%0], {%1,%2,%3,%4}, [%5];" ::"r"(a), "r"(x), "r"(y), "r"(z), "r"(w), "r"(bar) : "memory");
}
__device__ __forceinline__ void wait_bar(uint32_t bar) {
    uint32_t done = 0;
    for (int it = 0; it < (1 << 22); it++) {
        asm volatile("{ .reg .pred p; mbarrier.try_wait.parity.acquire.cluster.shared::cta.b64 p, [%1], 0; selp.u32 %0, 1, 0, p; }" : "=r"(done) : "r"(bar) : "memory");
        if (done) break;
    }
}
__device__ __forceinline__ void bar_sync(int id, int n) { asm volatile("bar.sync %0, %1;" ::"r"(id), "r"(n) : "memory"); }
__device__ __forceinline__ bool bar_and(int id, bool v) {
    uint32_t r;
    asm volatile("{ .reg .pred p, q; setp.ne.u32 p, %2, 0; barrier.cta.red.and.aligned.pred q, %1, 128, p; selp.u32 %0, 1, 0, q; }" : "=r"(r) : "r"(id), "r"((uint32_t)v) : "memory");
    return r;
}
__device__ __forceinline__ void bar_arrive(int id, int n) { asm volatile("bar.arrive %0, %1;" ::"r"(id), "r"(n) : "memory"); }
__device__ __forceinline__ void tma3d(uint32_t dst, const CUtensorMap* m, int c0, int c1, uint32_t bar) {
    asm volatile("cp.async.bulk.tensor.3d.shared::cluster.global.mbarrier::complete_tx::bytes [%0], [%1, {%3, %4, %5}], [%2];" ::"r"(dst), "l"(m), "r"(bar), "r"(c0), "r"(c1), "r"(0) : "memory");
}

template <int OFF, int SC>
__device__ __forceinline__ void wgmma32(float (&d)[128], uint32_t a0, uint32_t a1, uint32_t a2, uint32_t a3, uint32_t dlo) {
    if constexpr (SC == 0)
    asm volatile("{ .reg .b64 dsc; mov.b64 dsc, {%20, 8};\n wgmma.mma_async.sync.aligned.m64n32k16.f32.bf16.bf16 {%0, %1, %2, %3, %4, %5, %6, %7, %8, %9, %10, %11, %12, %13, %14, %15}, {%16, %17, %18, %19}, dsc, 0, 1, 1, 0; }"
                 : "=f"(d[OFF + 0]), "=f"(d[OFF + 1]), "=f"(d[OFF + 2]), "=f"(d[OFF + 3]), "=f"(d[OFF + 4]), "=f"(d[OFF + 5]), "=f"(d[OFF + 6]), "=f"(d[OFF + 7]), "=f"(d[OFF + 8]), "=f"(d[OFF + 9]), "=f"(d[OFF + 10]), "=f"(d[OFF + 11]), "=f"(d[OFF + 12]), "=f"(d[OFF + 13]), "=f"(d[OFF + 14]), "=f"(d[OFF + 15])
                 : "r"(a0), "r"(a1), "r"(a2), "r"(a3), "r"(dlo));
    else
    asm volatile("{ .reg .b64 dsc; mov.b64 dsc, {%20, 8};\n wgmma.mma_async.sync.aligned.m64n32k16.f32.bf16.bf16 {%0, %1, %2, %3, %4, %5, %6, %7, %8, %9, %10, %11, %12, %13, %14, %15}, {%16, %17, %18, %19}, dsc, %21, 1, 1, 0; }"
                 : "+f"(d[OFF + 0]), "+f"(d[OFF + 1]), "+f"(d[OFF + 2]), "+f"(d[OFF + 3]), "+f"(d[OFF + 4]), "+f"(d[OFF + 5]), "+f"(d[OFF + 6]), "+f"(d[OFF + 7]), "+f"(d[OFF + 8]), "+f"(d[OFF + 9]), "+f"(d[OFF + 10]), "+f"(d[OFF + 11]), "+f"(d[OFF + 12]), "+f"(d[OFF + 13]), "+f"(d[OFF + 14]), "+f"(d[OFF + 15])
                 : "r"(a0), "r"(a1), "r"(a2), "r"(a3), "r"(dlo), "n"(SC & 1));
}
#define WG_FENCE asm volatile("wgmma.fence.sync.aligned;" ::: "memory");
#define WG_COMMIT asm volatile("wgmma.commit_group.sync.aligned;" ::: "memory");
#define WG_WAIT(n) asm volatile("wgmma.wait_group.sync.aligned %0;" ::"n"(n) : "memory");

template <int J, int B, int NB>
__device__ __forceinline__ void step_ranges(float (&d)[128], uint32_t (&a)[32], uint32_t desc) {
    if constexpr (B < NB) {
        wgmma32<16 * B, J != 0>(d, a[4 * (J & 7)], a[4 * (J & 7) + 1], a[4 * (J & 7) + 2], a[4 * (J & 7) + 3], desc + (32 * B + 16 * J));
        step_ranges<J, B + 1, NB>(d, a, desc);
    }
}
template <int P>
__device__ __forceinline__ void group(float (&d)[128], uint32_t (&a)[32], uint32_t desc) {
    WG_FENCE
    step_ranges<2 * P, 0, 8 - P>(d, a, desc);
    step_ranges<2 * P + 1, 0, 8 - P>(d, a, desc);
    WG_COMMIT
}
template <int HI, int LO>
__device__ __forceinline__ void first(float (&d)[128], uint32_t (&a)[32], uint32_t desc) {
    wgmma32<16 * HI, 2>(d, a[0], a[1], a[2], a[3], desc + 32 * HI);
    wgmma32<16 * HI, 1>(d, a[4], a[5], a[6], a[7], desc + 32 * HI + 16);
    if constexpr (HI > LO) first<HI - 1, LO>(d, a, desc);
}
template <int B>
__device__ __forceinline__ void epi(float (&d)[128], uint32_t& carry, uint32_t pw) {
    uint32_t r[4];
#pragma unroll
    for (int k = 3; k >= 0; k--) {
        const int i = 4 * B + k;
        r[k] = pack(d[4 * i], d[4 * i + 1]);
        if (i < 31) r[k] = hadd(r[k], carry);
        if (i > 0) carry = pack(d[4 * i + 2], d[4 * i + 3]);
    }
    asm volatile("stmatrix.sync.aligned.m8n8.x4.trans.shared.b16 [%0], {%1,%2,%3,%4};" ::"r"(pw - B * 512), "r"(r[0]), "r"(r[1]), "r"(r[2]), "r"(r[3]) : "memory");
}
template <int P>
__device__ __forceinline__ void loadA(uint32_t (&a)[32], uint32_t ax) {
#pragma unroll
    for (int j = 2 * P; j < 2 * P + 2; j++) {
        a[4 * (j & 7)] = lds32(ax + 256 * j);
        a[4 * (j & 7) + 1] = lds32(ax + 256 * j + 128);
        a[4 * (j & 7) + 2] = lds32(ax + 256 * j + 16);
        a[4 * (j & 7) + 3] = lds32(ax + 256 * j + 144);
    }
}
__device__ __forceinline__ void reduce_push(uint32_t pr, uint32_t dst, uint32_t bar) {
    uint4 p0 = lds128(pr), p1 = lds128(pr + PS), p2 = lds128(pr + 2 * PS), p3 = lds128(pr + 3 * PS);
    st_async(dst, hadd(hadd(p0.x, p1.x), hadd(p2.x, p3.x)), hadd(hadd(p0.y, p1.y), hadd(p2.y, p3.y)),
             hadd(hadd(p0.z, p1.z), hadd(p2.z, p3.z)), hadd(hadd(p0.w, p1.w), hadd(p2.w, p3.w)), bar);
}

struct C2 { uint32_t re, im; };
__device__ __forceinline__ C2 cmul(C2 a, uint32_t s) {
    C2 r;
    asm("{ .reg .b16 l, h; .reg .b32 sl, sh, t, u, v;\n mov.b32 {l, h}, %4; mov.b32 sl, {l, l}; mov.b32 sh, {h, h};\n"
        "mul.rn.bf16x2 t, %3, sh; mul.bf16x2 u, %2, sl; sub.bf16x2 %0, u, t;\n"
        "mul.rn.bf16x2 v, %3, sl; fma.rn.bf16x2 %1, %2, sh, v; }" : "=r"(r.re), "=r"(r.im) : "r"(a.re), "r"(a.im), "r"(s));
    return r;
}
__device__ __forceinline__ void csq(float& re, float& im) { float t = re + re; re = fmaf(re, re, -im * im); im = t * im; }
__device__ __forceinline__ float ex2(float x) { float r; asm("ex2.approx.ftz.f32 %0, %1;" : "=f"(r) : "f"(x)); return r; }
__device__ __forceinline__ void st2(uint32_t are, uint32_t aim, C2 a, C2 b, C2 c, C2 d) { sts128(are, a.re, b.re, c.re, d.re); sts128(aim, a.im, b.im, c.im, d.im); }
struct KParams { uint32_t p[6], ldt, dsk; };
__device__ __forceinline__ void kgen_load(KParams& k, const Params& prm, int ch, int tid) {
    const size_t po = (size_t)ch * 256 + tid * 2;
    k.ldt = ldg16(prm.log_dt + ch);
    k.p[0] = ldg32(prm.a_re + po); k.p[1] = ldg32(prm.a_im + po); k.p[2] = ldg32(prm.b_re + po);
    k.p[3] = ldg32(prm.b_im + po); k.p[4] = ldg32(prm.c_re + po); k.p[5] = ldg32(prm.c_im + po);
    k.dsk = ldg16(prm.dskip + ch);
}
__device__ __forceinline__ void wgmma48(float (&d)[24], uint32_t da, uint32_t db, uint32_t sc) {
    asm volatile("{ .reg .b64 da, db; .reg .pred p; setp.ne.u32 p, %26, 0; mov.b64 da, {%24, 128}; mov.b64 db, {%25, 128};\n wgmma.mma_async.sync.aligned.m64n48k16.f32.bf16.bf16 {%0,%1,%2,%3,%4,%5,%6,%7,%8,%9,%10,%11,%12,%13,%14,%15,%16,%17,%18,%19,%20,%21,%22,%23}, da, db, p, 1, 1, 1, 1; }"
                 : "+f"(d[0]), "+f"(d[1]), "+f"(d[2]), "+f"(d[3]), "+f"(d[4]), "+f"(d[5]), "+f"(d[6]), "+f"(d[7]), "+f"(d[8]), "+f"(d[9]), "+f"(d[10]), "+f"(d[11]), "+f"(d[12]), "+f"(d[13]), "+f"(d[14]), "+f"(d[15]), "+f"(d[16]), "+f"(d[17]), "+f"(d[18]), "+f"(d[19]), "+f"(d[20]), "+f"(d[21]), "+f"(d[22]), "+f"(d[23]) : "r"(da), "r"(db), "r"(sc));
}
__device__ __forceinline__ void wait48(float (&d)[24]) {
    asm volatile("wgmma.wait_group.sync.aligned 0;" : "+f"(d[0]), "+f"(d[1]), "+f"(d[2]), "+f"(d[3]), "+f"(d[4]), "+f"(d[5]), "+f"(d[6]), "+f"(d[7]), "+f"(d[8]), "+f"(d[9]), "+f"(d[10]), "+f"(d[11]), "+f"(d[12]), "+f"(d[13]), "+f"(d[14]), "+f"(d[15]), "+f"(d[16]), "+f"(d[17]), "+f"(d[18]), "+f"(d[19]), "+f"(d[20]), "+f"(d[21]), "+f"(d[22]), "+f"(d[23]) :: "memory");
}
__device__ __forceinline__ void kext(float (&v)[6], const float (&d)[24]) {
    v[0] = d[0] - d[14]; v[1] = d[1] - d[15]; v[2] = d[4] - d[18]; v[3] = d[5] - d[19]; v[4] = d[8] - d[22]; v[5] = d[9] - d[23];
}
__device__ __forceinline__ void kgen_batch(const KParams& k, int b, uint32_t gb, int tid, int barid, float (&d)[24] TSARG) {
    const float dt = __bfloat162float(__float2bfloat16_rn(expf(blo(k.ldt))));
    const float dl = dt * 1.4426950408889634f;
    const uint32_t tb = gb + tid * 16, tp = tb;
    const uint32_t dsc = ((gb & 0x3FFFF) >> 4) | 0x80000;
    const uint32_t sel = b ? 0x3244 : 0x1044;
    const float al = __uint_as_float(prmt(k.p[0], 0, sel)) * dl, om = __uint_as_float(prmt(k.p[1], 0, sel)) * dt;
    const float br = __uint_as_float(prmt(k.p[2], 0, sel)) * dt, bi = __uint_as_float(prmt(k.p[3], 0, sel)) * dt;
    const float cr = __uint_as_float(prmt(k.p[4], 0, sel)), ci = __uint_as_float(prmt(k.p[5], 0, sel));
    const float wr = fmaf(cr, br, -ci * bi), wi = fmaf(cr, bi, ci * br);
    const float r1 = ex2(al), r64 = ex2(al * 64.f);
    float re = r1 * __cosf(om), im = r1 * __sinf(om);
    float hr = r64 * __cosf(om * 64.f), hi = r64 * __sinf(om * 64.f);
    const uint32_t s1 = pack(re, im);
    csq(re, im);
    const uint32_t s2 = pack(re, im);
    csq(re, im);
    C2 qa; qa.re = pack(wr, fmaf(wr, re, -wi * im)); qa.im = pack(wi, fmaf(wr, im, wi * re));
    csq(re, im);
    C2 p0; p0.re = pack(1.f, re); p0.im = pack(0.f, im);
    csq(re, im);
    const uint32_t s16 = pack(re, im);
    csq(re, im);
    uint32_t s32 = pack(re, im);
    const uint32_t s64 = pack(hr, hi);
    csq(hr, hi);
    const uint32_t s128 = pack(hr, hi);
    csq(hr, hi);
    const uint32_t s256 = pack(hr, hi);
    csq(hr, hi);
    const uint32_t s512 = pack(hr, hi);
    csq(hr, hi);
    uint32_t s1024 = pack(hr, hi);
    asm volatile("{ .reg .pred p; setp.ne.u32 p, %0, 0x7fc17fc1; @p wgmma.wait_group.sync.aligned 0; }" ::"r"(s1024) : "memory");
    bar_sync(barid, 128);
    const C2 p1 = cmul(p0, s16), p2 = cmul(p0, s32), p3 = cmul(p1, s32);
    st2(tp, tp + 2048, p0, p1, p2, p3);
    st2(tp + 8192, tp + 10240, cmul(p0, s128), cmul(p1, s128), cmul(p2, s128), cmul(p3, s128));
    const C2 p4 = cmul(p0, s64), p5 = cmul(p1, s64), p6 = cmul(p2, s64), p7 = cmul(p3, s64);
    st2(tp + 4096, tp + 6144, p4, p5, p6, p7);
    st2(tp + 12288, tp + 14336, cmul(p4, s128), cmul(p5, s128), cmul(p6, s128), cmul(p7, s128));
    KSTAMP(17 + 3 * b);
    const C2 qb = cmul(qa, s2), qg = cmul(qa, s512);
    st2(tb + 16384, tb + 22528, qa, qb, cmul(qa, s1), cmul(qb, s1));
    st2(tb + 18432, tb + 24576, cmul(qa, s256), cmul(qb, s256), qg, cmul(qg, s256));
    C2 qf; qf.re = prmt(qa.re, qg.re, 0x5410); qf.im = prmt(qa.im, qg.im, 0x5410);
    const C2 qh = cmul(qf, s1024), qi = cmul(qh, s1024);
    st2(tb + 20480, tb + 26624, qh, cmul(qh, s256), qi, qi);
    asm volatile("fence.proxy.async.shared::cta;" ::: "memory");
    bar_sync(barid, 128);
    KSTAMP(18 + 3 * b);
    WG_FENCE
#pragma unroll
    for (int s = 0; s < 8; s++) wgmma48(d, dsc + 16 * s, dsc + 1024 + 16 * s, s ? 1 : b);
    WG_COMMIT
}
template <class F>
__device__ __forceinline__ void kgen(const KParams& k, uint32_t gb, int tid, int barid, uint32_t (&o)[3], F&& mid TSARG) {
    float d[24], u[6];
#pragma unroll
    for (int i = 0; i < 24; i++) d[i] = 0.f;
#pragma unroll 1
    for (int b = 0; b < 2; b++) {
        kgen_batch(k, b, gb, tid, barid, d TSPASS);
        if (b == 0) mid();
    }
    wait48(d);
    kext(u, d);
    if (tid == 0) u[0] += blo(k.dsk);
    o[0] = pack(u[0], u[1]); o[1] = pack(u[2], u[3]); o[2] = pack(u[4], u[5]);
    KSTAMP(22);
}
__device__ __forceinline__ void kexpand(const uint32_t (&o)[3], uint32_t zb, uint32_t ke, int w, int lane, int barid TSARG) {
    {
        const int t = lane & 3, b = 8 * w + (lane >> 2);
        const uint32_t z0 = zb + 16 * b + 4 * (t & 1) + (t & 2);
        const uint32_t z1 = zb + (t < 2 ? 512 + 8 * b + 2 * t : 512 + 128 * t + 4 * b);
        const uint32_t z2 = zb + 1024 + (t == 2 ? 256 : 64 * t) + 2 * b;
        sts16(z0, o[0]); sts16(z0 + 8, o[0] >> 16);
        sts16(z1, o[1]); sts16(z1 + (t < 2 ? 4 : 2), o[1] >> 16);
        if (t < 3) sts16(z2, o[2]);
        if (t < 2) sts16(z2 + 128, o[2] >> 16);
    }
    if (barid < 3) KSTAMP(11);
    bar_sync(barid, 128);
    if (barid < 3) KSTAMP(12);
    uint32_t e0, e1, e2, e3, o0, o1, o2, o3;
    const uint32_t zc = zb + 1024 + (w * 32 + lane) * 2;
    const uint32_t v0 = lds16(zc), v1 = lds16(zc + 2);
    if (w & 2) {
        const uint32_t za = zb + 768 + ((w - 2) * 32 + lane) * 4;
        const uint32_t v = lds32(za), v2 = lds32(za + 4);
        e0 = prmt(v, 0, 0x1010); e1 = v; e2 = prmt(v, 0, 0x3232); e3 = prmt(v2, 0, 0x1010);
        o0 = e0; o1 = e0; o2 = e2; o3 = prmt(v, v2, 0x5432);
    } else if (w & 1) {
        const uint2 v = lds64(zb + 512 + lane * 8);
        const uint32_t v4 = lds32(zb + 512 + lane * 8 + 8), pv = lds32(zb + 508);
        e0 = prmt(v.x, 0, 0x1010); e1 = prmt(v.x, v.y, 0x5432); e2 = prmt(v.y, 0, 0x1010); e3 = prmt(v.y, v4, 0x5432);
        o0 = lane ? e0 : prmt(pv, v.x, 0x5432); o1 = v.x; o2 = e2; o3 = v.y;
    } else {
        const uint4 e = lds128(zb + lane * 16);
        uint32_t p = lds32(zb + lane * 16 - 4);
        if (lane == 0) p = 0;
        e0 = e.x; e1 = e.y; e2 = e.z; e3 = e.w;
        o0 = prmt(p, e.x, 0x5432); o1 = prmt(e.x, e.y, 0x5432); o2 = prmt(e.y, e.z, 0x5432); o3 = prmt(e.z, e.w, 0x5432);
    }
    if (w == 3 && lane < 2) sts128(ke + lane * 4160, 0, 0, 0, 0);
    ke += 16 + w * 512 + lane * 16;
    sts128(ke, e0, e1, e2, e3);
    sts128(ke + 4160, o0, o1, o2, o3);
    const uint32_t d0 = v0 * 0x10001u, d1 = v1 * 0x10001u, m = v0 | (v1 << 16);
    sts128(ke + 2048, d0, d0, (lane & 1) ? d1 : m, d1);
    sts128(ke + 2048 + 4160, d0, d0, (lane & 1) ? m : d0, d1);
}

template <bool GATE>
__device__ __forceinline__ void final_pass(uint32_t ybase, uint32_t qbase, __nv_bfloat16* outp, int i0, int i1, int lane) {
    const int r = lane & 7, k = lane >> 3, g = lane >> 2, t = lane & 3;
    const int ch = 8 * ((r >> 1) & 1) + 2 * k + (r & 1);
    const uint32_t ya = ybase + ch * 1040 + (ch >> 3) * 64 + (r >> 2) * 32;
    const uint32_t qa = qbase + g * 1056 + (t >> 1) * 64 + (t & 1) * 16;
    char* op = (char*)outp + (size_t)(16 * (t >> 1) + g) * 1792 + (t & 1) * 16;
#pragma unroll 2
    for (int i = i0; i < i1; i += 4) {
        const int c = (i & 1) + 4 * (i >> 1);
        uint32_t v0, v1, v2, v3;
        asm volatile("ldmatrix.sync.aligned.m8n8.x4.trans.shared.b16 {%0,%1,%2,%3}, [%4];" : "=r"(v0), "=r"(v1), "=r"(v2), "=r"(v3) : "r"(ya + c * 16));
        if (GATE) {
            uint4 q = lds128(qa + c * 32);
            v0 = hmul(v0, q.x); v1 = hmul(v1, q.y); v2 = hmul(v2, q.z); v3 = hmul(v3, q.w);
        }
        asm volatile("st.global.v4.b32 [%0], {%1,%2,%3,%4};" ::"l"(op + (size_t)c * (8 * 1792)), "r"(v0), "r"(v1), "r"(v2), "r"(v3) : "memory");
    }
}

__device__ __forceinline__ void push4(uint32_t dd, const uint32_t (&R)[8], uint32_t bx) {
    st_async(dd, prmt(R[7], R[6], 0x5410), prmt(R[5], R[4], 0x5410), prmt(R[3], R[2], 0x5410), prmt(R[1], R[0], 0x5410), bx);
    st_async(dd + XS, prmt(R[7], R[6], 0x7632), prmt(R[5], R[4], 0x7632), prmt(R[3], R[2], 0x7632), prmt(R[1], R[0], 0x7632), bx);
}
__device__ __forceinline__ void expect_tx(uint32_t bar, uint32_t n) { asm volatile("mbarrier.arrive.expect_tx.shared.b64 _, [%0], %1;" ::"r"(bar), "r"(n) : "memory"); }
__device__ __forceinline__ void bulk_g2s(uint32_t dst, const void* src, uint32_t n, uint32_t bar) {
    asm volatile("cp.async.bulk.shared::cluster.global.mbarrier::complete_tx::bytes [%0], [%1], %2, [%3];" ::"r"(dst), "l"(src), "r"(n), "r"(bar) : "memory");
}

__device__ __forceinline__ void warp_arrive(uint32_t bar, int lane) {
    __syncwarp();
    if (lane == 0) asm volatile("mbarrier.arrive.shared.b64 _, [%0];" ::"r"(bar) : "memory");
}

__global__ void __cluster_dims__(4, 1, 1) __launch_bounds__(384, 1) fused_kernel(const __grid_constant__ Params prm, const __grid_constant__ Maps mp) {
    extern __shared__ __align__(1024) char smem[];
    asm volatile("griddepcontrol.launch_dependents;");
    const uint32_t base = (uint32_t)__cvta_generic_to_shared(smem);
    const uint32_t bars = base + O_BAR;
    const int wg = __shfl_sync(0xffffffff, threadIdx.x >> 7, 0);
    const int tid = threadIdx.x & 127, lane = threadIdx.x & 31;
    const int w = __shfl_sync(0xffffffff, tid >> 5, 0);
    const int rank = blockIdx.x & 3, cl = blockIdx.x >> 2;
    const int ch0 = 4 * blockIdx.x;
    TSINIT(base + (wg == 0 ? O_YB + 16688 : wg == 1 ? O_YA + 16688 : O_YB + 16736), wg == 2 ? O_YA - 32 : 0)
    const unsigned t0 = clock();
    if (wg == 2) {
        if (lane == 0) {
            const uint32_t bw = bars + 32 * w, cnt = w == 3 ? 4 : 1;
#pragma unroll
            for (int i = 0; i < 4; i++) asm volatile("mbarrier.init.shared.b64 [%0], %1;" ::"r"(bw + 8 * i), "r"(cnt) : "memory");
            asm volatile("fence.mbarrier_init.release.cluster;" ::: "memory");
            asm volatile("fence.proxy.async.shared::cta;" ::: "memory");
            if (w < 3) {
                expect_tx(bw, w == 0 ? RAWB : w == 1 ? 6144 : 16384);
                expect_tx(bw + 8, w == 0 ? 2 * RAWB : w == 1 ? 2048 : 8192);
                expect_tx(bw + 16, w == 2 ? 8192 + 2 * QB : 8192);
                expect_tx(bw + 24, 8192);
            }
        }
        __syncwarp();
    }
    asm volatile("barrier.cluster.arrive.relaxed.aligned;" ::: "memory");
    KParams kp;
    const uint32_t kdst = base + O_WG + O_KA + 16;
    const uint32_t wgb = base + O_WG + wg * WGR;
    if (wg == 2) asm volatile("setmaxnreg.dec.sync.aligned.u32 104;");
    kgen_load(kp, prm, ch0 + wg, tid);
    if (wg == 2) {
        if (w == 1 && lane < 30) {
            if (lane < 24) asm volatile("prefetch.global.L2 [%0];" ::"l"((&prm.a_re)[lane >> 2] + (ch0 + 3) * 256 + (lane & 3) * 64) : "memory");
            else if (lane < 28) asm volatile("prefetch.tensormap [%0];" ::"l"(&mp.mu + (lane - 24)) : "memory");
            else asm volatile("prefetch.global.L2 [%0];" ::"l"(lane == 28 ? prm.shift_k + 64 * cl : prm.ssm_D + ch0) : "memory");
        }
        if (tid == 0) {
            while ((unsigned)clock() - t0 < T_U) {}
            tma3d(base + O_YB, &mp.mu, 16 * cl, 64 * rank - 1, bars + B_U);
            bulk_g2s(kdst, prm.ssm_k + (size_t)ch0 * 2048, 4096, bars + B_S0);
            bulk_g2s(kdst + WGR, prm.ssm_k + (size_t)(ch0 + 2) * 2048, 4096, bars + B_S0);
            while ((unsigned)clock() - t0 < T_K) {}
            tma3d(base + O_YA, &mp.mk, 16 * cl, 64 * rank - 1, bars + B_KV);
            tma3d(base + O_RV, &mp.mv, 16 * cl, 64 * rank - 1, bars + B_KV);
        }
        __syncwarp();
    } else {
        if (lane < 17) sts128(base + O_XB + 32 * rank + (w < 2 ? wg + 2 * w : 2 + 2 * wg + w) * XS + 4096 + lane * 16, 0, 0, 0, 0);
    }
    asm volatile("barrier.cluster.wait.acquire.aligned;" ::: "memory");
    STAMP(wg, 0);
    {
        const int c4 = tid & 3, gam = tid >> 2;
        unsigned tag;
        uint32_t o[3];
        bool local = true;
#pragma unroll 1
        for (int job = 0; job < 2; job++) {
            const uint32_t roff = (gam + 1) * 32 + c4 * 8;
            const uint32_t xdst = mapa(base + 32 * c4 + 16 * (255 - 64 * rank - gam), c4);
            if (local) kgen(kp, wgb, tid, 1 + wg, o, [&] {
                if (wg != 2 || job) return;
                wait_bar(bars + B_U);
                STAMP(2, 1);
                {
                    uint32_t Rx[2][8], Ry[2][8];
#pragma unroll
                    for (int pass = 0; pass < 2; pass++)
#pragma unroll
                        for (int i = 0; i < 8; i++) { uint2 v = lds64(base + O_YB + roff + pass * 1024 + i * 2080); Rx[pass][i] = v.x; Ry[pass][i] = v.y; }
                    const uint32_t bx = mapa(bars + B_XB0, c4);
                    push4(xdst + O_XB, Rx[0], bx);
                    push4(xdst + O_XB - 512, Rx[1], bx);
                    push4(xdst + O_XB + 2 * XS, Ry[0], bx + 8);
                    push4(xdst + O_XB + 2 * XS - 512, Ry[1], bx + 8);
                }
                STAMP(2, 2);
            } TSPASS);
            if (wg != 2) {
                bar_arrive(7, 384);
                wait_bar(bars + B_XB0);
                asm volatile("fence.proxy.async.shared::cta;" ::: "memory");
                STAMP(wg, 10);
            } else if (job == 0) {
                STAMP(2, 3);
                const uint4 s0 = ldg128(prm.shift_k + (16 * cl + 4 * c4) * 4), s1 = ldg128(prm.shift_k + (16 * cl + 4 * c4) * 4 + 8);
                uint32_t dA = ldg32(prm.ssm_D + ch0 + (w & 2));
                tag = *(volatile unsigned*)&g_cnt[blockIdx.x];
#pragma unroll 1
                for (int st = 0; st < 2; st++) {
                    const uint32_t ka = kdst + (w >> 1) * WGR + st * KS + (w & 1) * 2048 + lane * 16;
                    wait_bar(bars + B_S0 + 8 * st);
                    asm volatile("" : "+r"(dA));
                    uint4 e[4];
                    uint32_t p[4];
#pragma unroll
                    for (int i = 0; i < 4; i++) { e[i] = lds128(ka + i * 512); p[i] = lds32(ka + i * 512 - 4); }
                    if ((w & 1) == 0 && lane == 0) {
                        e[0].x = (e[0].x & 0xffff0000u) | (pack(blo(e[0].x) + (st ? bhi(dA) : blo(dA)), 0.f) & 0xffffu);
                        p[0] = 0;
                        sts32(ka, e[0].x);
                        sts128(ka - 16, 0, 0, 0, 0);
                        sts128(ka - 16 + 4160, 0, 0, 0, 0);
                    }
#pragma unroll
                    for (int i = 0; i < 4; i++)
                        sts128(ka + i * 512 + 4160, prmt(p[i], e[i].x, 0x5432), prmt(e[i].x, e[i].y, 0x5432), prmt(e[i].y, e[i].z, 0x5432), prmt(e[i].z, e[i].w, 0x5432));
                    warp_arrive(bars + B_KA0 + 8 * st, lane);
                    STAMP(2, 6 + st);
                    if (st) break;
                    uint32_t W[4][2];
                    W[0][0] = prmt(s0.x, s0.z, 0x5410); W[1][0] = prmt(s0.x, s0.z, 0x7632); W[2][0] = prmt(s0.y, s0.w, 0x5410); W[3][0] = prmt(s0.y, s0.w, 0x7632);
                    W[0][1] = prmt(s1.x, s1.z, 0x5410); W[1][1] = prmt(s1.x, s1.z, 0x7632); W[2][1] = prmt(s1.y, s1.w, 0x5410); W[3][1] = prmt(s1.y, s1.w, 0x7632);
                    wait_bar(bars + B_KV);
                    STAMP(2, 4);
                    if (tid == 0) {
                        bulk_g2s(kdst + KS, prm.ssm_k + (size_t)(ch0 + 1) * 2048, 4096, bars + B_S1);
                        bulk_g2s(kdst + KS + WGR, prm.ssm_k + (size_t)(ch0 + 3) * 2048, 4096, bars + B_S1);
                    }
                    __syncwarp();
                    const uint32_t bx = mapa(bars + B_XA, c4);
#pragma unroll 1
                    for (int pass = 0; pass < 2; pass++) {
                        const uint32_t kb = base + O_YA + roff + pass * 1024, vb = base + O_RV + roff + pass * 1024;
                        uint2 k3 = lds64(kb - 32 + 5 * 2080), k2 = lds64(kb - 32 + 6 * 2080), k1 = lds64(kb - 32 + 7 * 2080);
                        uint32_t Rx[8], Ry[8];
#pragma unroll
                        for (int i = 0; i < 8; i++) {
                            uint2 k0 = lds64(kb + i * 2080), v = lds64(vb + i * 2080);
                            Rx[i] = hmul(hfma(k0.x, W[0][0], hfma(k1.x, W[1][0], hfma(k2.x, W[2][0], hmul(k3.x, W[3][0])))), v.x);
                            Ry[i] = hmul(hfma(k0.y, W[0][1], hfma(k1.y, W[1][1], hfma(k2.y, W[2][1], hmul(k3.y, W[3][1])))), v.y);
                            k3 = k2; k2 = k1; k1 = k0;
                        }
                        push4(xdst + O_XA - pass * 512, Rx, bx);
                        push4(xdst + O_XA + 2 * XS - pass * 512, Ry, bx);
                    }
                    STAMP(2, 5);
                }
                bar_sync(7, 384);
                if (tid == 0) {
                    tma3d(base + O_RV, &mp.mq, 16 * cl, 32 * rank, bars + B_YA1);
                    tma3d(base + O_RV + QB, &mp.mq, 16 * cl, 128 + 32 * rank, bars + B_YA1);
                }
                __syncwarp();
            }
            kexpand(o, wgb + TBL, wg == 2 ? base + O_WG + job * WGR + KS : wgb, w, lane, 1 + wg TSPASS);
            if (wg != 2) break;
            warp_arrive(bars + B_K2 + 8 * job, lane);
            STAMP(2, 8 + 2 * job);
            if (job == 0) {
                tag++;
                if (tid == 0) g_cnt[blockIdx.x] = tag;
                bool ok = false;
#pragma unroll 1
                for (int it = 0; it < HELP_POLLS && !ok; it++) {
                    uint32_t tg;
                    asm volatile("{ .reg .b128 v; .reg .b64 l, h; ld.relaxed.gpu.global.b128 v, [%4]; mov.b128 {l, h}, v; mov.b64 {%0, %1}, l; mov.b64 {%2, %3}, h; }"
                                 : "=r"(o[0]), "=r"(o[1]), "=r"(o[2]), "=r"(tg) : "l"(g_pkt + blockIdx.x * 128 + tid) : "memory");
                    ok = tg == tag;
                    if (!ok) __nanosleep(100);
                }
                local = !bar_and(3, ok);
                if (local) kgen_load(kp, prm, ch0 + 3, tid);
                STAMP(2, 9);
            }
        }
    }
    if (wg == 2) {
#pragma unroll 1
        for (int s = 0; s < 2; s++) {
            wait_bar(bars + B_YA1 + 8 * s);
            STAMP(wg, 11 + 4 * s);
            final_pass<true>(base + O_YA, base + O_RV + s * (QB - 1024), prm.out + (size_t)(256 * rank + 768 * s) * 896 + 16 * cl, w + 16 * s, 16 + 16 * s, lane);
        }
        STAMP(wg, 12);
#pragma unroll 1
        for (int s = 0; s < 3; s++) {
            wait_bar(bars + (s ? B_YB2 - 8 + 8 * s : B_YB1));
            if (s == 2) STAMP(wg, 13);
            const int row0 = s == 0 ? 256 * rank : s == 1 ? 768 + 192 * rank : 1344 + 64 * rank;
            final_pass<false>(base + O_YB, 0, prm.out + (size_t)row0 * 896 + 448 + 16 * cl, w + (s ? 4 + 12 * s : 0), s == 0 ? 16 : 24 + 4 * s, lane);
        }
        STAMP(wg, 14);
    } else {
        KSTAMP(23);
        asm volatile("setmaxnreg.inc.sync.aligned.u32 200;");
        const int g = lane >> 2, t = lane & 3;
        const uint32_t xb = base + O_XB + 32 * rank;
        const uint32_t aoff = wgb + 16 + ((g & 1) ? 0 : 4160) + 4 * (8 * w + t + (g >> 1) - 3);
        const uint32_t pw = wgb + O_PART + w * PS + 16 * (255 + 2 * w - lane);
        const uint32_t pr = wgb + O_PART + tid * 16;
        const uint32_t yloc = base + (4 * rank * 1040 + (rank >> 1) * 64);
        const int r2 = w == 3 ? lane >> 3 : tid / 24;
        const uint32_t yB0 = mapa(yloc + O_YB + lane * 16, w), yB1 = mapa(yloc + O_YB + (w == 3 ? 56 + (lane & 7) : 32 + tid - 24 * r2) * 16, r2);
        const uint32_t bl = bars & 0xffffff;
        bar_sync(1 + wg, 128);
        STAMP(wg, 1);
        float d[128];
        uint32_t a[32];
        uint32_t carry = 0;
        uint32_t y1 = 0, b1 = 0;
        uint32_t axc = aoff;
        uint32_t desc = (((xb + wg * XS) & 0x3FFFF) >> 4) | 0x10000;
        loadA<0>(a, axc); loadA<1>(a, axc); loadA<2>(a, axc); loadA<3>(a, axc);
        STAMP(wg, 2);
        group<0>(d, a, desc);
        group<1>(d, a, desc);
        if (lane < 2 * w) sts128(wgb + O_PART + w * PS + lane * 16, 0, 0, 0, 0);
#pragma unroll
        for (int c = 0; c < 4; c++) {
            const bool isB = (c == 0) | (c == 3);
            const int chl = isB ? (c ? 2 + wg : wg) : c - 1 + 2 * wg;
            const uint32_t axn = aoff + (c == 2 ? KS : O_KA + c * KS);
            const uint32_t descn = (((xb + (c == 2 ? 2 + wg : 4 + c + 2 * wg) * XS) & 0x3FFFF) >> 4) | 0x10000;
            if (c) {
                bar_sync(1 + wg, 128);
                reduce_push(pr + 2048, y1, b1);
            }
            bar_sync(1 + wg, 128);
#define STAGE(P, N) WG_WAIT(N) epi<7 - P>(d, carry, pw);
            STAGE(0, 1) loadA<4>(a, axc); group<2>(d, a, desc);
            STAGE(1, 1) loadA<5>(a, axc); group<3>(d, a, desc);
            STAGE(2, 1) loadA<6>(a, axc); group<4>(d, a, desc);
            STAGE(3, 1) loadA<7>(a, axc); group<5>(d, a, desc);
            {
                const uint32_t y0 = yB0 + (isB ? 0 : O_YA - O_YB) + chl * 1040;
                y1 = isB ? yB1 + chl * 1040 : y0 + 512;
                b1 = (y1 & 0xff000000u) | (bl + (isB ? (w == 3 ? B_YB3 : B_YB2) : B_YA2));
                bar_sync(1 + wg, 128);
                reduce_push(pr, y0, (y0 & 0xff000000u) | (bl + (isB ? B_YB1 : B_YA1)));
            }
            STAGE(4, 1)
            STAMP(wg, 3 + 2 * c);
            if (c == 3) break;
            wait_bar(bars + B_KA0 + 8 * c + (c == 2 ? 8 * wg : 0));
            loadA<0>(a, axn);
            group<6>(d, a, desc);
            STAGE(5, 1)
            loadA<1>(a, axn);
            if (c == 0) {
                wait_bar(bars + B_XB1);
                wait_bar(bars + B_XA);
                asm volatile("fence.proxy.async.shared::cta;" ::: "memory");
            }
            STAMP(wg, 4 + 2 * c);
            WG_FENCE
            step_ranges<14, 0, 1>(d, a, desc);
            step_ranges<15, 0, 1>(d, a, desc);
            first<7, 4>(d, a, descn);
            WG_COMMIT
            STAGE(6, 1)
            loadA<2>(a, axn);
            WG_FENCE
            first<3, 1>(d, a, descn);
            WG_COMMIT
            STAGE(7, 1)
            loadA<3>(a, axn);
            WG_FENCE
            first<0, 0>(d, a, descn);
            WG_COMMIT
            group<1>(d, a, descn);
            axc = axn;
            desc = descn;
        }
        group<6>(d, a, desc);
        STAGE(5, 1)
        group<7>(d, a, desc);
        STAGE(6, 1)
        bar_sync(1 + wg, 128);
        if (w < 3) reduce_push(pr + 2048, y1, b1);
        STAGE(7, 0)
        bar_sync(1 + wg, 128);
        if (w == 3) reduce_push(pr + 2048, y1, b1);
        STAMP(wg, 15);
    }
    TSFLUSH(blockIdx.x);
}

__global__ void __launch_bounds__(128 * HELP_WG, 1) helper_kernel(const __grid_constant__ Params prm) {
    extern __shared__ __align__(1024) char smem[];
    const uint32_t base = (uint32_t)__cvta_generic_to_shared(smem);
    const int grp = __shfl_sync(0xffffffff, threadIdx.x >> 7, 0);
    const int tid = threadIdx.x & 127;
    const int hi = grp * NHELP + blockIdx.x;
    TSINIT(base + HELP_WG * TBL + grp * 64, 0)
    KParams kp;
    if (hi < 112) {
        kgen_load(kp, prm, 4 * hi + 3, tid);
        unsigned tag = *(volatile unsigned*)&g_cnt[112 + hi];
        uint32_t o[3];
        kgen(kp, base + grp * TBL, tid, 1 + grp, o, [] {} TSPASS);
        tag++;
        if (tid == 0) g_cnt[112 + hi] = tag;
        asm volatile("{ .reg .b128 v; .reg .b64 l, h; mov.b64 l, {%0, %1}; mov.b64 h, {%2, %3}; mov.b128 v, {l, h}; st.relaxed.gpu.global.b128 [%4], v; }"
                     ::"r"(o[0]), "r"(o[1]), "r"(o[2]), "r"(tag), "l"(g_pkt + hi * 128 + tid) : "memory");
        STAMP(0, 23);
        TSFLUSH(112 + blockIdx.x);
    }
}

typedef CUresult (*EncodeFn)(CUtensorMap*, CUtensorMapDataType, cuuint32_t, void*, const cuuint64_t*, const cuuint64_t*, const cuuint32_t*, const cuuint32_t*,
                             CUtensorMapInterleave, CUtensorMapSwizzle, CUtensorMapL2promotion, CUtensorMapFloatOOBfill);

}

static void launch_on(void* const* d_in, void* d_out, cudaStream_t st) {
    static EncodeFn enc = nullptr;
    if (!enc) {
        cudaDriverEntryPointQueryResult qr;
        cudaGetDriverEntryPoint("cuTensorMapEncodeTiled", (void**)&enc, cudaEnableDefault, &qr);
        cudaFuncSetAttribute(fused_kernel, cudaFuncAttributeMaxDynamicSharedMemorySize, SMEM_BYTES);
        cudaFuncSetAttribute(helper_kernel, cudaFuncAttributeMaxDynamicSharedMemorySize, HELP_SMEM);
    }
    Params p;
    Maps mp;
    CUtensorMap* maps[4] = {&mp.mq, &mp.mk, &mp.mv, &mp.mu};
    void* ptrs[4] = {d_in[0], d_in[1], d_in[2], d_in[6]};
    for (int i = 0; i < 4; i++) {
        cuuint64_t gd[3] = {448, 256, 8}, gs[2] = {7168, 896};
        cuuint32_t bx[3] = {16, i ? 65u : 33u, 8}, es[3] = {1, 1, 1};
        enc(maps[i], CU_TENSOR_MAP_DATA_TYPE_BFLOAT16, 3, ptrs[i], gd, gs, bx, es, CU_TENSOR_MAP_INTERLEAVE_NONE, CU_TENSOR_MAP_SWIZZLE_NONE,
            CU_TENSOR_MAP_L2_PROMOTION_NONE, CU_TENSOR_MAP_FLOAT_OOB_FILL_NONE);
    }
    const __nv_bfloat16* const* q = (const __nv_bfloat16* const*)d_in;
    p.shift_k = q[3]; p.ssm_k = q[4]; p.ssm_D = q[5];
    p.a_re = q[7]; p.a_im = q[8]; p.b_re = q[9]; p.b_im = q[10]; p.c_re = q[11]; p.c_im = q[12]; p.log_dt = q[13]; p.dskip = q[14];
    p.out = (__nv_bfloat16*)d_out;
    fused_kernel<<<112, 384, SMEM_BYTES, st>>>(p, mp);
    cudaLaunchConfig_t cfg = {};
    cfg.gridDim = dim3(NHELP); cfg.blockDim = dim3(128 * HELP_WG); cfg.dynamicSmemBytes = HELP_SMEM; cfg.stream = st;
    cudaLaunchAttribute at[1];
    at[0].id = cudaLaunchAttributeProgrammaticStreamSerialization; at[0].val.programmaticStreamSerializationAllowed = 1;
    cfg.attrs = at; cfg.numAttrs = 1;
    cudaLaunchKernelEx(&cfg, helper_kernel, p);
}

extern "C" void kernel_launch(void* const* d_in, const int* in_sizes, int n_in, void* d_out, int out_size) {
    launch_on(d_in, d_out, cudaStreamPerThread);
}
```

```cpp
#include <cuda_runtime.h>
#include <cuda_bf16.h>
#include <cuda.h>
#include <stdint.h>

namespace {

constexpr int XS = 4480;
constexpr int KS = 8320;
constexpr int PS = 4224;
constexpr int TBL = 4 * PS;
constexpr int O_PART = 2 * KS;
constexpr int O_KA = O_PART + 18432;
constexpr int WGR = O_KA + 2 * KS;
constexpr int RAWB = 16384;
constexpr int RAWK = 17408;
constexpr int QB = 9216;
constexpr int O_YB = 0;
constexpr int O_YA = 16640;
constexpr int O_RV = O_YA + RAWK;
constexpr int O_XB = O_RV + 3 * QB;
constexpr int O_XA = O_XB + 4 * XS;
constexpr int O_WG = O_XA + 4 * XS;
constexpr int O_PT = O_WG + 2 * WGR;
constexpr int O_BAR = O_PT + TBL;
constexpr int O_SM = O_BAR + 160;
constexpr int SMEM_BYTES = O_SM + 144;
static_assert(SMEM_BYTES <= 232448 && O_RV % 256 == 0 && O_XB % 128 == 0, "smem");
enum { B_U = 0, B_KV = 8, B_S0 = 16, B_S1 = 24, B_YB1 = 32, B_YB2 = 40, B_YB3 = 48, B_XB0 = 72, B_XB1 = 80, B_XA0 = 88, B_YA1 = 96, B_YA2 = 104, B_XA1 = 112, B_KA0 = 120, B_KA1 = 128, B_K2 = 136, B_K3 = 144 };
#define HELP_POLLS 60
#define PF 0
#define NS 0
#define T_U 500
#define T_K 600
constexpr int NHELP = 20;
constexpr int HELP_WG = 6;
constexpr int HELP_SMEM = HELP_WG * TBL + 512;

__device__ uint4 g_pkt[112 * 256];
__device__ unsigned g_cnt[224];

struct Params {
    uint32_t lo[8], hi[4];
    const __nv_bfloat16 *shift_k, *ssm_k, *ssm_D;
    __nv_bfloat16* out;
    uint4* pkt;
    unsigned* cnt;
};
struct Maps { CUtensorMap mu, mk, mv, mq, mo; };

#define STH 32
#define STAMP(role, i)
#define KSTAMP(i)
#define TSARG
#define TSPASS
#define TSINIT(addr, off)
#define TSFLUSH(blk)

__device__ __forceinline__ int tidx() { int t; asm volatile("mov.u32 %0, %%tid.x;" : "=r"(t)); return t; }
__device__ __forceinline__ uint32_t lds32(uint32_t a) { uint32_t v; asm volatile("ld.shared.u32 %0, [%1];" : "=r"(v) : "r"(a)); return v; }
__device__ __forceinline__ uint32_t lds16(uint32_t a) { uint16_t v; asm volatile("ld.shared.u16 %0, [%1];" : "=h"(v) : "r"(a)); return v; }
__device__ __forceinline__ uint2 lds64(uint32_t a) { uint2 v; asm volatile("ld.shared.v2.u32 {%0,%1}, [%2];" : "=r"(v.x), "=r"(v.y) : "r"(a)); return v; }
__device__ __forceinline__ uint4 lds128(uint32_t a) { uint4 v; asm volatile("ld.shared.v4.u32 {%0,%1,%2,%3}, [%4];" : "=r"(v.x), "=r"(v.y), "=r"(v.z), "=r"(v.w) : "r"(a)); return v; }
__device__ __forceinline__ void sts16(uint32_t a, uint32_t v) { asm volatile("st.shared.u16 [%0], %1;" ::"r"(a), "h"((uint16_t)v) : "memory"); }
__device__ __forceinline__ void sts32(uint32_t a, uint32_t v) { asm volatile("st.shared.u32 [%0], %1;" ::"r"(a), "r"(v) : "memory"); }
__device__ __forceinline__ void sts64(uint32_t a, uint32_t x, uint32_t y) { asm volatile("st.shared.v2.u32 [%0], {%1,%2};" ::"r"(a), "r"(x), "r"(y) : "memory"); }
__device__ __forceinline__ void sts128(uint32_t a, uint32_t x, uint32_t y, uint32_t z, uint32_t w) { asm volatile("st.shared.v4.u32 [%0], {%1,%2,%3,%4};" ::"r"(a), "r"(x), "r"(y), "r"(z), "r"(w) : "memory"); }
__device__ __forceinline__ uint32_t ldg16(const void* p) { uint16_t v; asm volatile("ld.global.nc.u16 %0, [%1];" : "=h"(v) : "l"(p)); return v; }
__device__ __forceinline__ uint32_t ldg32(const void* p) { uint32_t v; asm volatile("ld.global.nc.u32 %0, [%1];" : "=r"(v) : "l"(p)); return v; }
__device__ __forceinline__ uint2 ldg64(const void* p) { uint2 v; asm volatile("ld.global.nc.v2.u32 {%0,%1}, [%2];" : "=r"(v.x), "=r"(v.y) : "l"(p)); return v; }
__device__ __forceinline__ uint4 ldg128(const void* p) { uint4 v; asm volatile("ld.global.nc.v4.u32 {%0,%1,%2,%3}, [%4];" : "=r"(v.x), "=r"(v.y), "=r"(v.z), "=r"(v.w) : "l"(p)); return v; }
__device__ __forceinline__ uint32_t pack(float lo, float hi) { uint32_t r; asm("cvt.rn.bf16x2.f32 %0, %1, %2;" : "=r"(r) : "f"(hi), "f"(lo)); return r; }
__device__ __forceinline__ uint32_t hadd(uint32_t a, uint32_t b) { uint32_t r; asm("add.rn.bf16x2 %0, %1, %2;" : "=r"(r) : "r"(a), "r"(b)); return r; }
__device__ __forceinline__ uint32_t hmul(uint32_t a, uint32_t b) { uint32_t r; asm("mul.rn.bf16x2 %0, %1, %2;" : "=r"(r) : "r"(a), "r"(b)); return r; }
__device__ __forceinline__ uint32_t hfma(uint32_t a, uint32_t b, uint32_t c) { uint32_t r; asm("fma.rn.bf16x2 %0, %1, %2, %3;" : "=r"(r) : "r"(a), "r"(b), "r"(c)); return r; }
__device__ __forceinline__ uint32_t hneg(uint32_t a) { uint32_t r; asm("neg.bf16x2 %0, %1;" : "=r"(r) : "r"(a)); return r; }
__device__ __forceinline__ uint32_t prmt(uint32_t a, uint32_t b, uint32_t s) { uint32_t r; asm("prmt.b32 %0, %1, %2, %3;" : "=r"(r) : "r"(a), "r"(b), "r"(s)); return r; }
__device__ __forceinline__ float blo(uint32_t v) { return __uint_as_float(v << 16); }
__device__ __forceinline__ float bhi(uint32_t v) { return __uint_as_float(v & 0xffff0000u); }
__device__ __forceinline__ uint32_t mapa(uint32_t a, uint32_t r) { uint32_t o; asm("mapa.shared::cluster.u32 %0, %1, %2;" : "=r"(o) : "r"(a), "r"(r)); return o; }
__device__ __forceinline__ void st_async(uint32_t a, uint32_t x, uint32_t y, uint32_t z, uint32_t w, uint32_t bar) {
    asm volatile("st.async.weak.shared::cluster.mbarrier::complete_tx::bytes.v4.b32 [%0], {%1,%2,%3,%4}, [%5];" ::"r"(a), "r"(x), "r"(y), "r"(z), "r"(w), "r"(bar) : "memory");
}
__device__ __forceinline__ void wait_bar(uint32_t bar) {
    uint32_t done = 0;
    for (int it = 0; it < (1 << 22); it++) {
        asm volatile("{ .reg .pred p; mbarrier.try_wait.parity.shared::cta.b64 p, [%1], 0; selp.u32 %0, 1, 0, p; }" : "=r"(done) : "r"(bar) : "memory");
        if (done) break;
    }
}
__device__ __forceinline__ void bar_sync(int id, int n) { asm volatile("bar.sync %0, %1;" ::"r"(id), "r"(n) : "memory"); }
__device__ __forceinline__ bool bar_and(int id, bool v) {
    uint32_t r;
    asm volatile("{ .reg .pred p, q; setp.ne.u32 p, %2, 0; barrier.cta.red.and.aligned.pred q, %1, 128, p; selp.u32 %0, 1, 0, q; }" : "=r"(r) : "r"(id), "r"((uint32_t)v) : "memory");
    return r;
}
__device__ __forceinline__ void bar_arrive(int id, int n) { asm volatile("bar.arrive %0, %1;" ::"r"(id), "r"(n) : "memory"); }
__device__ __forceinline__ void tma3d(uint32_t dst, const CUtensorMap* m, int c0, int c1, uint32_t bar) {
    asm volatile("cp.async.bulk.tensor.3d.shared::cluster.global.mbarrier::complete_tx::bytes [%0], [%1, {%3, %4, %5}], [%2];" ::"r"(dst), "l"(m), "r"(bar), "r"(c0), "r"(c1), "r"(0) : "memory");
}

template <int OFF, int SC>
__device__ __forceinline__ void wgmma32(float (&d)[128], uint32_t a0, uint32_t a1, uint32_t a2, uint32_t a3, uint64_t dlo) {
    if constexpr (SC == 0)
    asm volatile("{ wgmma.mma_async.sync.aligned.m64n32k16.f32.bf16.bf16 {%0, %1, %2, %3, %4, %5, %6, %7, %8, %9, %10, %11, %12, %13, %14, %15}, {%16, %17, %18, %19}, %20, 0, 1, 1, 0; }"
                 : "=f"(d[OFF + 0]), "=f"(d[OFF + 1]), "=f"(d[OFF + 2]), "=f"(d[OFF + 3]), "=f"(d[OFF + 4]), "=f"(d[OFF + 5]), "=f"(d[OFF + 6]), "=f"(d[OFF + 7]), "=f"(d[OFF + 8]), "=f"(d[OFF + 9]), "=f"(d[OFF + 10]), "=f"(d[OFF + 11]), "=f"(d[OFF + 12]), "=f"(d[OFF + 13]), "=f"(d[OFF + 14]), "=f"(d[OFF + 15])
                 : "r"(a0), "r"(a1), "r"(a2), "r"(a3), "l"(dlo));
    else
    asm volatile("{ wgmma.mma_async.sync.aligned.m64n32k16.f32.bf16.bf16 {%0, %1, %2, %3, %4, %5, %6, %7, %8, %9, %10, %11, %12, %13, %14, %15}, {%16, %17, %18, %19}, %20, %21, 1, 1, 0; }"
                 : "+f"(d[OFF + 0]), "+f"(d[OFF + 1]), "+f"(d[OFF + 2]), "+f"(d[OFF + 3]), "+f"(d[OFF + 4]), "+f"(d[OFF + 5]), "+f"(d[OFF + 6]), "+f"(d[OFF + 7]), "+f"(d[OFF + 8]), "+f"(d[OFF + 9]), "+f"(d[OFF + 10]), "+f"(d[OFF + 11]), "+f"(d[OFF + 12]), "+f"(d[OFF + 13]), "+f"(d[OFF + 14]), "+f"(d[OFF + 15])
                 : "r"(a0), "r"(a1), "r"(a2), "r"(a3), "l"(dlo), "n"(SC & 1));
}
template <int OFF>
__device__ __forceinline__ void wgmma16(float (&d)[128], uint32_t a0, uint32_t a1, uint32_t a2, uint32_t a3, uint64_t dlo) {
    asm volatile("{ wgmma.mma_async.sync.aligned.m64n16k16.f32.bf16.bf16 {%0, %1, %2, %3, %4, %5, %6, %7}, {%8, %9, %10, %11}, %12, 1, 1, 1, 0; }"
                 : "+f"(d[OFF + 0]), "+f"(d[OFF + 1]), "+f"(d[OFF + 2]), "+f"(d[OFF + 3]), "+f"(d[OFF + 4]), "+f"(d[OFF + 5]), "+f"(d[OFF + 6]), "+f"(d[OFF + 7])
                 : "r"(a0), "r"(a1), "r"(a2), "r"(a3), "l"(dlo));
}
#define WG_FENCE asm volatile("wgmma.fence.sync.aligned;" ::: "memory");
#define WG_COMMIT asm volatile("wgmma.commit_group.sync.aligned;" ::: "memory");
#define WG_WAIT(n) asm volatile("wgmma.wait_group.sync.aligned %0;" ::"n"(n) : "memory");

template <int J, int B, int NB>
__device__ __forceinline__ void step_ranges(float (&d)[128], uint32_t (&a)[32], uint64_t desc) {
    if constexpr (B < NB) {
        if constexpr ((J & 1) && B == NB - 1) wgmma16<16 * B>(d, a[4 * (J & 7)], a[4 * (J & 7) + 1], a[4 * (J & 7) + 2], a[4 * (J & 7) + 3], desc + (32 * B + 16 * J));
        else wgmma32<16 * B, J != 0>(d, a[4 * (J & 7)], a[4 * (J & 7) + 1], a[4 * (J & 7) + 2], a[4 * (J & 7) + 3], desc + (32 * B + 16 * J));
        step_ranges<J, B + 1, NB>(d, a, desc);
    }
}
template <int P>
__device__ __forceinline__ void group(float (&d)[128], uint32_t (&a)[32], uint64_t desc) {
    WG_FENCE
    step_ranges<2 * P, 0, 8 - P>(d, a, desc);
    step_ranges<2 * P + 1, 0, 8 - P>(d, a, desc);
    WG_COMMIT
}
template <int B, int J, int JE>
__device__ __forceinline__ void range_steps(float (&d)[128], uint32_t (&a)[32], uint64_t desc) {
    if constexpr (J == JE) wgmma16<16 * B>(d, a[4 * (J & 7)], a[4 * (J & 7) + 1], a[4 * (J & 7) + 2], a[4 * (J & 7) + 3], desc + (32 * B + 16 * J));
    else {
        wgmma32<16 * B, 1>(d, a[4 * (J & 7)], a[4 * (J & 7) + 1], a[4 * (J & 7) + 2], a[4 * (J & 7) + 3], desc + (32 * B + 16 * J));
        range_steps<B, J + 1, JE>(d, a, desc);
    }
}
template <int J, int HI, int LO>
__device__ __forceinline__ void pair(float (&d)[128], uint32_t (&a)[32], uint64_t desc) {
    wgmma32<16 * HI, 1>(d, a[4 * J], a[4 * J + 1], a[4 * J + 2], a[4 * J + 3], desc + (32 * HI + 16 * J));
    if constexpr (J + 2 * HI == 14) wgmma16<16 * HI>(d, a[4 * J + 4], a[4 * J + 5], a[4 * J + 6], a[4 * J + 7], desc + (32 * HI + 16 * J + 16));
    else wgmma32<16 * HI, 1>(d, a[4 * J + 4], a[4 * J + 5], a[4 * J + 6], a[4 * J + 7], desc + (32 * HI + 16 * J + 16));
    if constexpr (HI > LO) pair<J, HI - 1, LO>(d, a, desc);
}
template <int HI, int LO>
__device__ __forceinline__ void first(float (&d)[128], uint32_t (&a)[32], uint64_t desc) {
    wgmma32<16 * HI, 2>(d, a[0], a[1], a[2], a[3], desc + 32 * HI);
    if constexpr (HI == 7) wgmma16<16 * HI>(d, a[4], a[5], a[6], a[7], desc + 32 * HI + 16);
    else wgmma32<16 * HI, 1>(d, a[4], a[5], a[6], a[7], desc + 32 * HI + 16);
    if constexpr (HI > LO) first<HI - 1, LO>(d, a, desc);
}
struct Epi { uint32_t carry, c2, own[4], pw, pr; bool hi; int w; };
template <int B>
__device__ __forceinline__ void epi(float (&d)[128], Epi& e) {
    uint32_t& carry = e.carry;
    uint32_t r[4];
#pragma unroll
    for (int k = 3; k >= 0; k--) {
        const int i = 4 * B + k;
        r[k] = pack(d[4 * i], d[4 * i + 1]);
        if (i < 31) r[k] = hadd(r[k], carry);
        if (i > 0) carry = pack(d[4 * i + 2], d[4 * i + 3]);
    }
    const uint32_t p0 = e.hi ? r[1] : r[0], p1 = e.hi ? r[2] : r[1], p2 = e.hi ? r[3] : r[2], p3 = e.hi ? (B == 7 ? 0 : e.c2) : r[3];
    e.c2 = r[0];
    asm volatile("{ .reg .pred p; setp.eq.u32 p, %8, %9; @!p st.shared.v4.u32 [%10], {%4, %5, %6, %7};\n"
                 "@p mov.b32 %0, %4; @p mov.b32 %1, %5; @p mov.b32 %2, %6; @p mov.b32 %3, %7; }"
                 : "+r"(e.own[0]), "+r"(e.own[1]), "+r"(e.own[2]), "+r"(e.own[3])
                 : "r"(p0), "r"(p1), "r"(p2), "r"(p3), "r"(e.w), "n"((7 - B) & 3), "r"((e.pw ^ (((7 - B) & 3) << 9)) + (7 - B) * 2048) : "memory");
}
template <int P>
__device__ __forceinline__ void loadA(uint32_t (&a)[32], uint32_t ax) {
#pragma unroll
    for (int j = 2 * P; j < 2 * P + 2; j++) {
        a[4 * (j & 7)] = lds32(ax + 256 * j);
        a[4 * (j & 7) + 1] = lds32(ax + 256 * j + 128);
        a[4 * (j & 7) + 2] = lds32(ax + 256 * j + 16);
        a[4 * (j & 7) + 3] = lds32(ax + 256 * j + 144);
    }
}
__device__ __forceinline__ void reduce_push(const Epi& e, int half, uint32_t dst, uint32_t bar) {
    const uint4 p0 = make_uint4(e.own[0], e.own[1], e.own[2], e.own[3]);
    const uint4 p1 = lds128(e.pr + 8192 * half + 512), p2 = lds128(e.pr + 8192 * half + 1024), p3 = lds128(e.pr + 8192 * half + 1536);
    st_async(dst, hadd(hadd(p0.x, p1.x), hadd(p2.x, p3.x)), hadd(hadd(p0.y, p1.y), hadd(p2.y, p3.y)),
             hadd(hadd(p0.z, p1.z), hadd(p2.z, p3.z)), hadd(hadd(p0.w, p1.w), hadd(p2.w, p3.w)), bar);
}

struct C2 { uint32_t re, im; };
__device__ __forceinline__ C2 cmul(C2 a, uint32_t s) {
    C2 r;
    asm("{ .reg .b16 l, h; .reg .b32 sl, sh, t, u, v;\n mov.b32 {l, h}, %4; mov.b32 sl, {l, l}; mov.b32 sh, {h, h};\n"
        "mul.rn.bf16x2 t, %3, sh; mul.bf16x2 u, %2, sl; sub.bf16x2 %0, u, t;\n"
        "mul.rn.bf16x2 v, %3, sl; fma.rn.bf16x2 %1, %2, sh, v; }" : "=r"(r.re), "=r"(r.im) : "r"(a.re), "r"(a.im), "r"(s));
    return r;
}
__device__ __forceinline__ C2 cmul2(C2 a, uint32_t sr, uint32_t si) {
    C2 r;
    asm("{ .reg .b32 t, u, v;\n mul.rn.bf16x2 t, %3, %5; mul.bf16x2 u, %2, %4; sub.bf16x2 %0, u, t;\n"
        "mul.rn.bf16x2 v, %3, %4; fma.rn.bf16x2 %1, %2, %5, v; }" : "=r"(r.re), "=r"(r.im) : "r"(a.re), "r"(a.im), "r"(sr), "r"(si));
    return r;
}
__device__ __forceinline__ void csq(float& re, float& im) { float t = re + re; re = fmaf(re, re, -im * im); im = t * im; }
__device__ __forceinline__ float ex2(float x) { float r; asm("ex2.approx.ftz.f32 %0, %1;" : "=f"(r) : "f"(x)); return r; }
__device__ __forceinline__ void st2(uint32_t are, uint32_t aim, C2 a, C2 b, C2 c, C2 d) { sts128(are, a.re, b.re, c.re, d.re); sts128(aim, a.im, b.im, c.im, d.im); }
__device__ __forceinline__ uint4 ldm4t(uint32_t a) {
    uint4 v;
    asm volatile("ldmatrix.sync.aligned.m8n8.x4.trans.shared.b16 {%0,%1,%2,%3}, [%4];" : "=r"(v.x), "=r"(v.y), "=r"(v.z), "=r"(v.w) : "r"(a) : "memory");
    return v;
}
__device__ __forceinline__ uint32_t ldm1t(uint32_t a) {
    uint32_t v;
    asm volatile("ldmatrix.sync.aligned.m8n8.x1.trans.shared.b16 {%0}, [%1];" : "=r"(v) : "r"(a) : "memory");
    return v;
}
__device__ __forceinline__ void hmma(float* d, uint32_t a0, uint32_t a1, uint32_t a2, uint32_t a3, uint32_t b0, uint32_t b1) {
    asm("mma.sync.aligned.m16n8k16.row.col.f32.bf16.bf16.f32 {%0,%1,%2,%3}, {%4,%5,%6,%7}, {%8,%9}, {%0,%1,%2,%3};"
        : "+f"(d[0]), "+f"(d[1]), "+f"(d[2]), "+f"(d[3]) : "r"(a0), "r"(a1), "r"(a2), "r"(a3), "r"(b0), "r"(b1));
}
struct KParams { uint32_t p[6], ldt, dsk; };
__device__ __forceinline__ const __nv_bfloat16* pptr(const Params& p, int i) {
    return (const __nv_bfloat16*)(((uint64_t)((i & 1) ? p.hi[i >> 1] >> 16 : p.hi[i >> 1] & 0xffffu) << 32) | p.lo[i]);
}
__device__ __forceinline__ void kgen_load(KParams& k, const Params& prm, int ch, int tid) {
    const size_t po = (size_t)ch * 256 + tid * 2;
    k.ldt = ldg16(pptr(prm, 6) + ch);
#pragma unroll
    for (int i = 0; i < 6; i++) k.p[i] = ldg32(pptr(prm, i) + po);
    k.dsk = ldg16(pptr(prm, 7) + ch);
}
template <bool X1>
__device__ __forceinline__ void kgen_batch(const KParams& k, int b, uint32_t tw, int lane, float (&d)[32], float& xs TSARG) {
    const float dt = __bfloat162float(__float2bfloat16_rn(expf(blo(k.ldt))));
    const float dl = dt * 1.4426950408889634f;
    const uint32_t tp = tw + lane * 16;
    const uint32_t sel = b ? 0x3244 : 0x1044;
    const float al = __uint_as_float(prmt(k.p[0], 0, sel)) * dl, om = __uint_as_float(prmt(k.p[1], 0, sel)) * dt;
    const float br = __uint_as_float(prmt(k.p[2], 0, sel)) * dt, bi = __uint_as_float(prmt(k.p[3], 0, sel)) * dt;
    const float cr = __uint_as_float(prmt(k.p[4], 0, sel)), ci = __uint_as_float(prmt(k.p[5], 0, sel));
    const float wr = fmaf(cr, br, -ci * bi), wi = fmaf(cr, bi, ci * br);
    const float r1 = ex2(al), r64 = ex2(al * 64.f);
    float re = r1 * __cosf(om), im = r1 * __sinf(om);
    float hr = r64 * __cosf(om * 64.f), hi = r64 * __sinf(om * 64.f);
    const uint32_t s1 = pack(re, im);
    csq(re, im);
    const uint32_t s2 = pack(re, im);
    csq(re, im);
    C2 qa; qa.re = pack(wr, fmaf(wr, re, -wi * im)); qa.im = pack(wi, fmaf(wr, im, wi * re));
    csq(re, im);
    C2 p0; p0.re = pack(1.f, re); p0.im = pack(0.f, -im);
    csq(re, im);
    const uint32_t s16 = pack(re, -im);
    csq(re, im);
    const uint32_t s32 = pack(re, -im);
    const uint32_t s64 = pack(hr, -hi);
    csq(hr, hi);
    csq(hr, hi);
    const uint32_t s256 = pack(hr, hi);
    csq(hr, hi);
    const uint32_t s512 = pack(hr, hi);
    csq(hr, hi);
    const uint32_t s1024 = pack(hr, hi);
    csq(hr, hi);
    xs = fmaf(wr, hr, fmaf(-wi, hi, xs));
    const uint32_t fa = tw + 3584 + (lane >> 4) * 64 + (lane & 6) * 8 + (lane & 8) + (lane & 1) * 2;
    __syncwarp();
    sts16(fa, s64); sts16(fa + 4, s64 >> 16);
    const C2 p1 = cmul(p0, s16);
    st2(tp, tp + 512, p0, p1, cmul(p0, s32), cmul(p1, s32));
    const C2 qb = cmul(qa, s2), qg = cmul(qa, s512);
    st2(tp + 1024, tp + 1536, qa, qb, cmul(qa, s1), cmul(qb, s1));
    st2(tp + 2048, tp + 2560, cmul(qa, s256), cmul(qb, s256), qg, cmul(qg, s256));
    C2 qf; qf.re = prmt(qa.re, qg.re, 0x5410); qf.im = prmt(qa.im, qg.im, 0x5410);
    const C2 qh = cmul(qf, s1024), qi = cmul(qh, s256);
    sts128(tp + 3072, qh.re, qi.re, qh.im, qi.im);
    __syncwarp();
    KSTAMP(17 + 3 * b);
    const uint32_t ta = tw + (lane >> 4) * 512 + (lane & 15) * 16;
    const uint4 q2 = ldm4t(tp + 3072);
#pragma unroll
    for (int s = 0; s < 2; s++) {
        const uint32_t t8 = tw + (lane & 7) * 16 + 256 * s;
        uint4 t1;
        if (X1) t1 = make_uint4(ldm1t(t8), ldm1t(t8 + 128), ldm1t(t8 + 512), ldm1t(t8 + 640));
        else t1 = ldm4t(ta + 256 * s);
        const uint4 f = lds128(tw + 3584 + 64 * s + (lane & 3) * 16);
        const uint4 q0 = ldm4t(ta + 1024 + 256 * s), q1 = ldm4t(ta + 2048 + 256 * s);
        C2 l[4], h[4];
        l[0].re = t1.x; l[0].im = t1.z; h[0].re = t1.y; h[0].im = t1.w;
        l[1] = cmul2(l[0], f.x, f.y); h[1] = cmul2(h[0], f.z, f.w);
        l[2] = cmul2(l[1], f.x, f.y); h[2] = cmul2(h[1], f.z, f.w);
        l[3] = cmul2(l[2], f.x, f.y); h[3] = cmul2(h[2], f.z, f.w);
#pragma unroll
        for (int m = 0; m < 2; m++) {
            const C2 a0 = l[2 * m], a1 = l[2 * m + 1], a2 = h[2 * m], a3 = h[2 * m + 1];
            hmma(d + 16 * m, a0.re, a1.re, a2.re, a3.re, q0.x, q0.y);
            hmma(d + 16 * m + 4, a0.re, a1.re, a2.re, a3.re, q1.x, q1.y);
            hmma(d + 16 * m + 8, a0.re, a1.re, a2.re, a3.re, s ? q2.z : q2.x, s ? q2.w : q2.y);
            hmma(d + 16 * m, a0.im, a1.im, a2.im, a3.im, q0.z, q0.w);
            hmma(d + 16 * m + 4, a0.im, a1.im, a2.im, a3.im, q1.z, q1.w);
            hmma(d + 16 * m + 12, a0.im, a1.im, a2.im, a3.im, s ? q2.z : q2.x, s ? q2.w : q2.y);
        }
    }
    KSTAMP(18 + 3 * b);
}
template <bool X1 = true, class F>
__device__ __forceinline__ void kgen(const KParams& k, uint32_t gb, int w, int lane, F&& mid TSARG) {
    float d[32], xs = 0.f;
    const uint32_t tw = gb + w * PS;
#pragma unroll
    for (int i = 0; i < 32; i++) d[i] = 0.f;
    if ((tidx() & 127) == 0) d[0] = blo(k.dsk);
#pragma unroll 1
    for (int b = 0; b < 2; b++) {
        kgen_batch<X1>(k, b, tw, lane, d, xs TSPASS);
        if (b == 0) mid();
    }
    {
        float c[4] = {0.f, 0.f, 0.f, 0.f}, e[4] = {0.f, 0.f, 0.f, 0.f};
        hmma(c, 0x3f803f80u, 0x3f803f80u, 0, 0, pack(xs, 0.f), 0);
        hmma(e, pack(c[0], c[1]), 0, 0, 0, 0x3f803f80u, 0);
        if (lane == 0) sts16(gb + 3840 + 2 * w, pack(e[0], 0.f));
    }
    __syncwarp();
#pragma unroll
    for (int n = 0; n < 3; n++) {
        uint32_t r[4];
#pragma unroll
        for (int m = 0; m < 4; m++) {
            const float* p = d + 16 * (m >> 1) + 4 * n + 2 * (m & 1);
            r[m] = (n == 2 && (lane & 2)) ? pack(p[4], p[5]) : pack(p[0], p[1]);
        }
        asm volatile("stmatrix.sync.aligned.m8n8.x4.shared.b16 [%0], {%1,%2,%3,%4};" ::"r"(tw + 512 * n + lane * 16), "r"(r[0]), "r"(r[1]), "r"(r[2]), "r"(r[3]) : "memory");
    }
    KSTAMP(22);
}
__device__ __forceinline__ void kfinish(uint32_t gb, int w, int lane, int barid, uint32_t (&o)[6] TSARG) {
    asm volatile("" : "+r"(lane));
    bar_sync(barid, 128);
    KSTAMP(19);
    const uint32_t za = gb + (w < 2 ? w : 2) * 512 + lane * 16;
    const uint4 p0 = lds128(za), p1 = lds128(za + PS), p2 = lds128(za + 2 * PS), p3 = lds128(za + 3 * PS);
    uint32_t x = lds32(w == 1 ? gb + (lane & 3) * PS + (lane < 4 ? 508 : 1024 + (lane & 8)) : gb + 3840 + (lane & 1) * 4);
    o[0] = hadd(hadd(p0.x, p1.x), hadd(p2.x, p3.x)); o[1] = hadd(hadd(p0.y, p1.y), hadd(p2.y, p3.y));
    o[2] = hadd(hadd(p0.z, p1.z), hadd(p2.z, p3.z)); o[3] = hadd(hadd(p0.w, p1.w), hadd(p2.w, p3.w));
    if (w == 0) {
        o[4] = __shfl_up_sync(0xffffffff, o[3], 1);
        if (lane == 0) o[4] = 0;
        o[5] = 0;
    } else if (w == 1) {
        o[4] = __shfl_sync(0xffffffff, lane ? prmt(o[0], o[2], 0x5410) : prmt(o[2], o[3], 0x5410), lane + 1);
        x = hadd(x, __shfl_xor_sync(0xffffffff, x, 1));
        x = hadd(x, __shfl_xor_sync(0xffffffff, x, 2));
        const uint32_t y = hadd(__shfl_sync(0xffffffff, x, 4), __shfl_sync(0xffffffff, x, 8)), n = __shfl_sync(0xffffffff, o[3], lane + 1);
        o[5] = prmt(lane == 31 ? y : n, lane ? o[0] << 16 : x, 0x7610);
    } else {
        const uint32_t y = hadd(x, __shfl_xor_sync(0xffffffff, x, 1)), s0 = hadd(o[0], o[2]), s1 = hadd(o[1], o[3]);
        o[0] = w == 2 ? s0 : s1;
        o[1] = __shfl_sync(0xffffffff, lane ? o[0] : w == 2 ? s1 : prmt(s0, hadd(y, y >> 16), 0x5432), lane + 1);
        o[4] = o[5] = 0;
    }
}
__device__ __forceinline__ void kexpand(const uint32_t (&o)[6], uint32_t ke, int w, int lane) {
    if (w == 3 && lane < 2) sts128(ke + lane * 4160, 0, 0, 0, 0);
    ke += 16 + lane * 16;
    if (w == 0) {
        sts128(ke, prmt(o[0], o[2], 0x5410), prmt(o[1], o[3], 0x5410), prmt(o[0], o[2], 0x7632), prmt(o[1], o[3], 0x7632));
        sts128(ke + 4160, prmt(o[4], o[0], 0x5432), prmt(o[2], o[1], 0x5410), prmt(o[3], o[0], 0x7610), prmt(o[2], o[1], 0x7632));
    } else if (w == 1) {
        const uint32_t z4 = prmt(o[0], 0, 0x3232);
        sts128(ke + 512, prmt(o[0], 0, 0x1010), prmt(o[1], o[0], 0x7610), z4, prmt(o[1], o[4], 0x5432));
        sts128(ke + 512 + 4160, prmt(o[5], o[0], 0x5432), prmt(o[0], o[1], 0x5410), z4, prmt(o[0], o[1], 0x7632));
#pragma unroll
        for (int i = 0; i < 2; i++) {
            const uint32_t v = o[2 + i], n = o[4 + i];
            const uint32_t y0 = prmt(v, 0, 0x1010), y4 = prmt(v, 0, 0x3232);
            sts128(ke + 1024 + 512 * i, y0, v, y4, prmt(n, 0, i ? 0x1010 : 0x3232));
            sts128(ke + 1024 + 512 * i + 4160, y0, y0, y4, prmt(v, n, i ? 0x5432 : 0x7632));
        }
    } else {
        ke += 1024 + 512 * w;
#pragma unroll
        for (int i = 0; i < 2; i++) {
            const uint32_t d0 = prmt(o[0], 0, i ? 0x3232 : 0x1010), d1 = prmt(o[1], 0, i ? 0x3232 : 0x1010), m = prmt(o[0], o[1], i ? 0x7632 : 0x5410);
            sts128(ke + 1024 * i, d0, d0, (lane & 1) ? d1 : m, d1);
            sts128(ke + 1024 * i + 4160, d0, d0, (lane & 1) ? m : d0, d1);
        }
    }
}

__device__ __forceinline__ void final_pass(uint32_t ybase, __nv_bfloat16* outp, int i0, int i1, int lane) {
    const int r = lane & 7, k = lane >> 3, g = lane >> 2, t = lane & 3;
    const int ch = 8 * ((r >> 1) & 1) + 2 * k + (r & 1);
    const uint32_t ya = ybase + ch * 1024, yx = (r >> 2) * 32 + (r & 1) * 16 + (r & 2) * 32;
    char* op = (char*)outp + (size_t)(64 * ((7 - g) >> 1) + 8 * (~g & 1) + 8 * (t & 2)) * 1792 + (t & 1) * 16;
#pragma unroll 1
    for (int i = i0; i < i1; i += 4) {
        const int c = (i & 1) + 4 * (i >> 1);
        uint32_t v0, v1, v2, v3;
        asm volatile("ldmatrix.sync.aligned.m8n8.x4.trans.shared.b16 {%0,%1,%2,%3}, [%4];" : "=r"(v0), "=r"(v1), "=r"(v2), "=r"(v3) : "r"(ya + (yx ^ (c * 16))));
        asm volatile("st.global.v4.b32 [%0], {%1,%2,%3,%4};" ::"l"(op + (size_t)(256 * (i >> 2) + 16 * (i & 2) + (i & 1)) * 1792), "r"(v0), "r"(v1), "r"(v2), "r"(v3) : "memory");
    }
}
template <bool GATE>
__device__ __forceinline__ void final_tma(uint32_t ybase, uint32_t tile, const CUtensorMap* m, int c0, int blk, int w, int lane) {
    const int r = lane & 7, k = lane >> 3, g = lane >> 2, t = lane & 3;
    const int ch = 8 * ((r >> 1) & 1) + 2 * k + (r & 1);
    const uint32_t ya = ybase + 128 * w + ch * 1024, yx = (r >> 2) * 32 + (r & 1) * 16 + (r & 2) * 32;
    const uint32_t ta = tile + ((7 - g) >> 1) * 2304 + (~g & 1) * 32 + w * 576 + (t >> 1) * 64 + (t & 1) * 16;
    uint32_t v[4][4];
    uint4 q[4];
#pragma unroll
    for (int j = 0; j < 4; j++) {
        const int c = (j & 1) + 4 * (j >> 1);
        asm volatile("ldmatrix.sync.aligned.m8n8.x4.trans.shared.b16 {%0,%1,%2,%3}, [%4];" : "=r"(v[j][0]), "=r"(v[j][1]), "=r"(v[j][2]), "=r"(v[j][3]) : "r"(ya + (yx ^ (c * 16))));
        if (GATE) q[j] = lds128(ta + (j & 1) * 288 + (j >> 1) * 128);
    }
#pragma unroll
    for (int j = 0; j < 4; j++) {
        if (GATE) { v[j][0] = hmul(v[j][0], q[j].x); v[j][1] = hmul(v[j][1], q[j].y); v[j][2] = hmul(v[j][2], q[j].z); v[j][3] = hmul(v[j][3], q[j].w); }
        sts128(ta + (j & 1) * 288 + (j >> 1) * 128, v[j][0], v[j][1], v[j][2], v[j][3]);
    }
    asm volatile("fence.proxy.async.shared::cta;" ::: "memory");
    bar_sync(3, 128);
    if (lane == 0) {
        asm volatile("cp.async.bulk.tensor.4d.global.shared::cta.bulk_group [%0, {%2, %3, %3, %4}], [%1];" ::"l"(m), "r"(tile + w * 2304), "r"(c0), "r"(0), "r"(blk + w) : "memory");
        asm volatile("cp.async.bulk.commit_group;" ::: "memory");
    }
    __syncwarp();
}

__device__ __forceinline__ void push4(uint32_t dd, const uint32_t (&R)[8], uint32_t bx) {
    st_async(dd, prmt(R[7], R[6], 0x5410), prmt(R[5], R[4], 0x5410), prmt(R[3], R[2], 0x5410), prmt(R[1], R[0], 0x5410), bx);
    st_async(dd + XS, prmt(R[7], R[6], 0x7632), prmt(R[5], R[4], 0x7632), prmt(R[3], R[2], 0x7632), prmt(R[1], R[0], 0x7632), bx);
}
__device__ __forceinline__ void expect_tx(uint32_t bar, uint32_t n) { asm volatile("mbarrier.arrive.expect_tx.shared.b64 _, [%0], %1;" ::"r"(bar), "r"(n) : "memory"); }
__device__ __forceinline__ void bulk_g2s(uint32_t dst, const void* src, uint32_t n, uint32_t bar) {
    asm volatile("cp.async.bulk.shared::cluster.global.mbarrier::complete_tx::bytes [%0], [%1], %2, [%3];" ::"r"(dst), "l"(src), "r"(n), "r"(bar) : "memory");
}

__device__ __forceinline__ void warp_arrive(uint32_t bar, int lane) {
    __syncwarp();
    if (lane == 0) asm volatile("mbarrier.arrive.shared.b64 _, [%0];" ::"r"(bar) : "memory");
}

__global__ void __cluster_dims__(4, 1, 1) __launch_bounds__(384, 1) fused_kernel(const __grid_constant__ Params prm, const __grid_constant__ Maps mp) {
    extern __shared__ __align__(1024) char smem[];
    asm volatile("griddepcontrol.launch_dependents;");
    KParams kp;
    if (threadIdx.x < 256) kgen_load(kp, prm, 4 * blockIdx.x + (threadIdx.x >> 7), threadIdx.x & 127);
    const uint32_t base = (uint32_t)__cvta_generic_to_shared(smem);
    const uint32_t bars = base + O_BAR;
    const int wg = __shfl_sync(0xffffffff, threadIdx.x >> 7, 0);
    const int tid = threadIdx.x & 127, lane = threadIdx.x & 31;
    const int w = __shfl_sync(0xffffffff, tid >> 5, 0);
    const int rank = blockIdx.x & 3, cl = blockIdx.x >> 2;
    const int ch0 = 4 * blockIdx.x;
    TSINIT(16384, 0)
    const unsigned t0 = clock();
    if (wg == 2) {
        asm volatile("setmaxnreg.dec.sync.aligned.u32 104;");
        const uint32_t bw = bars + 40 * w;
        if (lane == 0) {
            const uint32_t cnt = w == 3 ? 4 : 1;
#pragma unroll
            for (int i = 0; i < 5; i++) asm volatile("mbarrier.init.shared.b64 [%0], %1;" ::"r"(bw + 8 * i), "r"(cnt) : "memory");
            asm volatile("fence.mbarrier_init.release.cluster;" ::: "memory");
            asm volatile("fence.proxy.async.shared::cta;" ::: "memory");
        }
        __syncwarp();
        kgen_load(kp, prm, ch0 + 2, tid);
        if (lane == 0 && w < 3) {
            expect_tx(bw, w == 0 ? RAWB + 144 : w == 1 ? 4096 : 8192);
            expect_tx(bw + 8, w == 0 ? RAWB + RAWK : w == 1 ? 4096 : 8192);
            expect_tx(bw + 16, w == 0 ? 8192 : w == 1 ? 2048 : 8192 + 2 * QB);
            expect_tx(bw + 24, w == 1 ? 2048 : 8192);
            expect_tx(bw + 32, 8192);
        }
        __syncwarp();
    }
    asm volatile("barrier.cluster.arrive.relaxed.aligned;" ::: "memory");
    const uint32_t kdst = base + O_WG + O_KA + 16;
    const uint32_t wgb = base + O_WG + wg * WGR;
    if (wg == 2) {
        if (tid == 0) {
            while ((unsigned)clock() - t0 < T_U) {}
            tma3d(base + O_YB, &mp.mu, 16 * cl, 64 * rank, bars + B_U);
            bulk_g2s(base + O_SM, prm.shift_k + 64 * cl, 128, bars + B_U);
            bulk_g2s(base + O_SM + 128, prm.ssm_D + (ch0 & ~7), 16, bars + B_U);
            while ((unsigned)clock() - t0 < T_K) {}
            bulk_g2s(kdst, prm.ssm_k + (size_t)ch0 * 2048, 4096, bars + B_S0);
            bulk_g2s(kdst + WGR, prm.ssm_k + (size_t)(ch0 + 1) * 2048, 4096, bars + B_S0);
            tma3d(base + O_YA, &mp.mk, 16 * cl, 64 * rank - 4, bars + B_KV);
            tma3d(base + O_RV, &mp.mv, 16 * cl, 64 * rank, bars + B_KV);
        }
        __syncwarp();
    } else {
        if (wg == 0 && w == 1 && lane < 3) asm volatile("prefetch.global.L2 [%0];" ::"l"((&prm.shift_k)[lane] + (lane == 0 ? 64 * cl : lane == 1 ? ch0 * 2048 : ch0)) : "memory");
        if (wg == 1 && w == 1 && lane < 5) asm volatile("prefetch.tensormap [%0];" ::"l"(&mp.mu + lane) : "memory");
        if (lane < 17) sts128(base + O_XB + (wg + 2 * w) * XS + 4096 + lane * 16, 0, 0, 0, 0);
    }
    asm volatile("barrier.cluster.wait.acquire.aligned;" ::: "memory");
    STAMP(wg, 0);
    if (wg != 2) {
        {
            uint32_t o[6];
            kgen(kp, wgb + O_PART, w, lane, [] {} TSPASS);
            kfinish(wgb + O_PART, w, lane, 1 + wg, o TSPASS);
            STAMP(wg, 11);
            kexpand(o, wgb, w, lane);
            const uint32_t ka = wgb + O_KA + 16 + w * 1024 + lane * 16;
            wait_bar(bars + B_U);
            wait_bar(bars + B_S0);
            uint4 e0 = lds128(ka), e1 = lds128(ka + 512);
            uint32_t pv = 0;
            if (lane == 31 && w) pv = lds32(ka - 500);
            const uint32_t p0 = __shfl_sync(0xffffffff, lane == 31 ? pv : e0.w, lane - 1), p1 = __shfl_sync(0xffffffff, lane == 31 ? e0.w : e1.w, lane - 1);
            if ((tidx() & 127) == 0) {
                e0.x = (e0.x & 0xffff0000u) | (pack(blo(e0.x) + blo(lds16(base + O_SM + 128 + 2 * ((ch0 & 4) + wg))), 0.f) & 0xffffu);
                sts32(ka, e0.x);
                sts128(ka - 16, 0, 0, 0, 0);
                sts128(ka - 16 + 4160, 0, 0, 0, 0);
            }
            sts128(ka + 4160, prmt(p0, e0.x, 0x5432), prmt(e0.x, e0.y, 0x5432), prmt(e0.y, e0.z, 0x5432), prmt(e0.z, e0.w, 0x5432));
            sts128(ka + 512 + 4160, prmt(p1, e1.x, 0x5432), prmt(e1.x, e1.y, 0x5432), prmt(e1.y, e1.z, 0x5432), prmt(e1.z, e1.w, 0x5432));
        }
        KSTAMP(23);
        if (w == 0) {
            wait_bar(bars + B_XB0);
            asm volatile("fence.proxy.async.shared::cta;" ::: "memory");
        }
        asm volatile("setmaxnreg.inc.sync.aligned.u32 200;");
        const int g = lane >> 2, t = lane & 3;
        const uint32_t xb = base + O_XB;
        const uint32_t aoff = wgb + 16 + ((g & 1) ? 0 : 4160) + 4 * (8 * w + t + (g >> 1) - 3);
        const int tau = (w - t + 3) & 3, pos = 8 * (g >> 1) + 2 * tau + (g & 1);
        Epi e;
        e.carry = e.c2 = e.own[0] = e.own[1] = e.own[2] = e.own[3] = 0; e.pw = ((wgb + O_PART + 2047) & ~2047) + 16 * pos + 512 * w; e.pr = e.pw + 1536 * w;
        asm volatile("" : "+r"(e.pw), "+r"(e.pr)); e.hi = w > t; e.w = (tidx() >> 5) & 3;
        const uint32_t yloc = base + (4 * rank + wg) * 1024, yp = pos ^ (wg + 4 * (rank >> 1));
        int bid = 1 + wg;
        asm volatile("" : "+r"(bid));
        const uint32_t yB0 = mapa(yloc + O_YB + yp * 16, e.w), yB1 = mapa(yloc + O_YB + (32 + 8 * e.w + (yp & 7)) * 16, lane >> 3);
        const uint32_t bl = bars & 0xffffff;
        bar_sync(bid, 128);
        STAMP(wg, 1);
        float d[128];
        uint32_t a[32];
        uint32_t y1 = 0, b1 = 0;
        uint32_t axc = aoff;
        const uint64_t desc0 = (uint64_t)((((xb + wg * XS) & 0x3FFFF) >> 4) | 0x10000) | (8ull << 32);
        uint64_t desc = desc0;
        loadA<0>(a, axc); loadA<1>(a, axc);
        group<0>(d, a, desc);
        STAMP(wg, 2);
        loadA<2>(a, axc); loadA<3>(a, axc);
        group<1>(d, a, desc);
#pragma unroll
        for (int c = 0; c < 4; c++) {
            const bool isB = (c == 0) | (c == 3);
            const int chl = isB ? (c ? 2 : 0) : 2 * c - 2;
            const uint32_t axn = aoff + (c == 2 ? KS : O_KA + c * KS);
            const uint64_t descn = desc0 + (c == 2 ? 2 : 4 + 2 * c) * (XS / 16);
            if (c) {
                bar_sync(bid, 128);
                reduce_push(e, 1, y1, b1);
            }
#define STAGE(P, N) WG_WAIT(N) epi<7 - (P)>(d, e);
            if (c < 3) {
                STAGE(0, 1) loadA<4>(a, axc); group<2>(d, a, desc);
                STAGE(1, 1) loadA<5>(a, axc); group<3>(d, a, desc);
                STAGE(2, 1) loadA<6>(a, axc); group<4>(d, a, desc);
                STAGE(3, 1) loadA<7>(a, axc); group<5>(d, a, desc);
            } else {
                WG_FENCE pair<4, 3, 0>(d, a, desc); WG_COMMIT
                STAGE(0, 3) STAGE(1, 3) STAGE(2, 3) STAGE(3, 2)
                WG_FENCE pair<6, 3, 0>(d, a, desc); WG_COMMIT
            }
            {
                const uint32_t y0 = yB0 + (isB ? 0 : O_YA - O_YB) + chl * 1024;
                y1 = isB ? yB1 + chl * 1024 : y0 + 512;
                b1 = (y1 & 0xff000000u) | (bl + (isB ? B_YB2 + 4 * (w & 2) : B_YA2));
                bar_sync(bid, 128);
                reduce_push(e, 0, y0, (y0 & 0xff000000u) | (bl + (isB ? B_YB1 : B_YA1)));
            }
            if (c == 3) break;
            STAGE(4, 1)
            STAMP(wg, 3 + 2 * c);
            if (c) wait_bar(bars + B_KA0 + 8 * c + (c == 2 ? 8 * bid - 8 : 0));
            loadA<0>(a, axn);
            group<6>(d, a, desc);
            STAGE(5, 1)
            loadA<1>(a, axn);
            if (c == 0) {
                wait_bar(bars + B_XA0);
                asm volatile("fence.proxy.async.shared::cta;" ::: "memory");
            }
            STAMP(wg, 4 + 2 * c);
            WG_FENCE
            step_ranges<14, 0, 1>(d, a, desc);
            step_ranges<15, 0, 1>(d, a, desc);
            first<7, 4>(d, a, descn);
            WG_COMMIT
            STAGE(6, 1)
            loadA<2>(a, axn);
            WG_FENCE
            if (c == 2) { pair<2, 6, 4>(d, a, descn); pair<4, 5, 4>(d, a, descn); }
            first<3, 1>(d, a, descn);
            WG_COMMIT
            STAGE(7, 1)
            loadA<3>(a, axn);
            if (c < 2) {
                WG_FENCE
                first<0, 0>(d, a, descn);
                WG_COMMIT
                group<1>(d, a, descn);
            } else {
                WG_FENCE pair<6, 4, 4>(d, a, descn); WG_COMMIT
                WG_FENCE first<0, 0>(d, a, descn); pair<2, 3, 0>(d, a, descn); WG_COMMIT
            }
            axc = axn;
            desc = descn;
        }
        STAMP(wg, 9);
        WG_WAIT(2)
        loadA<4>(a, axc); loadA<5>(a, axc);
        WG_FENCE range_steps<3, 8, 9>(d, a, desc); WG_COMMIT
        WG_FENCE range_steps<2, 8, 11>(d, a, desc); WG_COMMIT
        WG_WAIT(3)
        loadA<6>(a, axc);
        WG_FENCE range_steps<1, 8, 13>(d, a, desc); WG_COMMIT
        WG_WAIT(3)
        loadA<7>(a, axc);
        WG_FENCE range_steps<0, 8, 15>(d, a, desc); WG_COMMIT
#define LAST(P) STAGE(4 + P, 3 - P) STAGE(5 + P, 2 - P) if ((w & 2) == P) { bar_sync(4 + 4 * bid + P, 128); reduce_push(e, 1, y1, b1); } else bar_arrive(4 + 4 * bid + P, 128);
        LAST(0) LAST(2)
        STAMP(wg, 15);
    } else {
    {
        const int c4 = (tid >> 3) & 3, gam = (tid & 7) + 8 * w;
        unsigned tag;
        uint32_t o[6];
        int job = 0;
        const uint32_t roff = gam * 32 + ((c4 * 8) ^ ((gam & 4) * 4));
        auto stage_u = [&] {
            const uint32_t xdst = mapa(base + 16 * (255 - 64 * rank - gam), c4);
            wait_bar(bars + B_U);
            STAMP(2, 1);
            uint32_t Rx[2][8], Ry[2][8];
#pragma unroll
            for (int pass = 0; pass < 2; pass++)
#pragma unroll
                for (int i = 0; i < 8; i++) { uint2 v = lds64(base + O_YB + roff + pass * 1024 + i * 2048); Rx[pass][i] = v.x; Ry[pass][i] = v.y; }
            const uint32_t bx = mapa(bars + B_XB0, c4);
            push4(xdst + O_XB, Rx[0], bx);
            push4(xdst + O_XB - 512, Rx[1], bx);
            push4(xdst + O_XB + 2 * XS, Ry[0], bx + 8);
            push4(xdst + O_XB + 2 * XS - 512, Ry[1], bx + 8);
            STAMP(2, 2);
        };
        auto odd = [&](int st) {
            const uint32_t ka = kdst + (w >> 1) * WGR + st * KS + (w & 1) * 2048 + lane * 16;
            wait_bar(bars + B_S0 + 8 * st);
            uint4 e[4];
            uint32_t p[4];
#pragma unroll
            for (int i = 0; i < 4; i++) e[i] = lds128(ka + i * 512);
            uint32_t e0 = 0;
            const int t63 = tidx() & 63;
            if (t63 == 63) e0 = lds32(ka - 500);
#pragma unroll
            for (int i = 0; i < 4; i++) p[i] = __shfl_sync(0xffffffff, lane == 31 ? (i ? e[i - 1].w : e0) : e[i].w, lane - 1);
            if (t63 == 0) {
                e[0].x = (e[0].x & 0xffff0000u) | (pack(blo(e[0].x) + blo(lds16(base + O_SM + 128 + 2 * ((ch0 & 4) + 2 * st) + w)), 0.f) & 0xffffu);
                sts32(ka, e[0].x);
                sts128(ka - 16, 0, 0, 0, 0);
                sts128(ka - 16 + 4160, 0, 0, 0, 0);
            }
#pragma unroll
            for (int i = 0; i < 4; i++)
                sts128(ka + i * 512 + 4160, prmt(p[i], e[i].x, 0x5432), prmt(e[i].x, e[i].y, 0x5432), prmt(e[i].y, e[i].z, 0x5432), prmt(e[i].z, e[i].w, 0x5432));
            if (st) {
                wait_bar(bars + B_XA1);
                wait_bar(bars + B_XB1);
                asm volatile("fence.proxy.async.shared::cta;" ::: "memory");
            }
            warp_arrive(bars + B_KA0 + 8 * st, lane);
            STAMP(2, 6 + st);
        };
        auto stage_kv = [&] {
            const int tv = tidx(), gam = (tv & 7) + ((tv >> 2) & 24);
            const uint32_t xdst = mapa(base + 16 * (255 - 64 * rank - gam), c4);
            const uint4 s0 = lds128(base + O_SM + 32 * c4), s1 = lds128(base + O_SM + 32 * c4 + 16);
            uint32_t W[4][2];
            W[0][0] = prmt(s0.x, s0.z, 0x5410); W[1][0] = prmt(s0.x, s0.z, 0x7632); W[2][0] = prmt(s0.y, s0.w, 0x5410); W[3][0] = prmt(s0.y, s0.w, 0x7632);
            W[0][1] = prmt(s1.x, s1.z, 0x5410); W[1][1] = prmt(s1.x, s1.z, 0x7632); W[2][1] = prmt(s1.y, s1.w, 0x5410); W[3][1] = prmt(s1.y, s1.w, 0x7632);
            wait_bar(bars + B_KV);
            STAMP(2, 4);
            if (tid == 0) {
                bulk_g2s(kdst + KS, prm.ssm_k + (size_t)(ch0 + 2) * 2048, 4096, bars + B_S1);
                bulk_g2s(kdst + KS + WGR, prm.ssm_k + (size_t)(ch0 + 3) * 2048, 4096, bars + B_S1);
            }
            __syncwarp();
            const uint32_t bx = mapa(bars + B_XA0, c4);
            uint32_t Ry[2][8];
#pragma unroll
            for (int pass = 0; pass < 2; pass++) {
                const uint32_t ko = base + O_YA + 128 + roff + pass * 1024, ke = base + O_YA + 128 + (roff ^ 16) + pass * 1024, vb = base + O_RV + roff + pass * 1024;
                const uint32_t hoff = (gam + 3) * 32 + ((c4 * 8) ^ (((gam + 3) & 4) * 4)), he = base + O_YA + hoff + pass * 1024, ho = base + O_YA + (hoff ^ 16) + pass * 1024;
                uint2 k3 = lds64(ho + 5 * 2176), k2 = lds64(he + 6 * 2176), k1 = lds64(ho + 7 * 2176);
                uint32_t Rx[8];
#pragma unroll
                for (int i = 0; i < 8; i++) {
                    uint2 k0 = lds64(((i & 1) ? ko : ke) + i * 2176), v = lds64(vb + i * 2048);
                    Rx[i] = hmul(hfma(k0.x, W[0][0], hfma(k1.x, W[1][0], hfma(k2.x, W[2][0], hmul(k3.x, W[3][0])))), v.x);
                    Ry[pass][i] = hmul(hfma(k0.y, W[0][1], hfma(k1.y, W[1][1], hfma(k2.y, W[2][1], hmul(k3.y, W[3][1])))), v.y);
                    k3 = k2; k2 = k1; k1 = k0;
                }
                push4(xdst + O_XA - pass * 512, Rx, bx);
            }
            STAMP(2, 5);
            push4(xdst + O_XA + 2 * XS, Ry[0], bx + (B_XA1 - B_XA0));
            push4(xdst + O_XA + 2 * XS - 512, Ry[1], bx + (B_XA1 - B_XA0));
        };
#pragma unroll 1
        for (;;) {
            const uint32_t tbl = wgb;
            kgen(kp, tbl, w, lane, [&] {
                if (job == 0) stage_u();
            } TSPASS);
            if (job == 0) {
                STAMP(2, 3);
                tag = *(volatile unsigned*)&prm.cnt[blockIdx.x];
                stage_kv();
                odd(1);
            }
            kfinish(tbl, w, lane, 3, o TSPASS);
            STAMP(wg, 11);
            if (job == 0) {
                if (tid == 0) {
#pragma unroll
                    for (int i = 0; i < 2; i++)
                        asm volatile("cp.async.bulk.tensor.4d.shared::cluster.global.mbarrier::complete_tx::bytes [%0], [%1, {%3, %4, %4, %5}], [%2];"
                                     ::"r"(base + O_RV + i * QB), "l"(&mp.mq), "r"(bars + B_YA1), "r"(16 * cl), "r"(0), "r"(16 * i + 4 * rank) : "memory");
                }
                __syncwarp();
            }
            bool fin, ok;
#pragma unroll 1
            do {
                kexpand(o, base + O_WG + job * WGR + KS, w, lane);
                fin = true;
                warp_arrive(bars + B_K2 + 8 * job, lane);
                STAMP(2, 8 + 2 * job);
                if (job) break;
                job = 1;
                tag++;
                if (tid == 0) prm.cnt[blockIdx.x] = tag;
                ok = false;
#pragma unroll 1
                for (int it = 0; it < HELP_POLLS && !ok; it++) {
                    uint32_t tg[2];
#pragma unroll
                    for (int i = 0; i < 2; i++)
                        asm volatile("{ .reg .b128 v; .reg .b64 l, h; ld.relaxed.gpu.global.b128 v, [%4]; mov.b128 {l, h}, v; mov.b64 {%0, %1}, l; mov.b64 {%2, %3}, h; }"
                                     : "=r"(o[3 * i]), "=r"(o[3 * i + 1]), "=r"(o[3 * i + 2]), "=r"(tg[i]) : "l"(prm.pkt + blockIdx.x * 256 + 128 * i + tid) : "memory");
                    ok = tg[0] == tag && tg[1] == tag;
                    if (!ok && NS) __nanosleep(NS);
                }
                fin = false;
                STAMP(2, 9);
            } while (bar_and(3, ok));
            if (fin) break;
            kgen_load(kp, prm, ch0 + 3, tid);
        }
    }
#pragma unroll 1
        for (int s = 0; s < 2; s++) {
            wait_bar(bars + B_YA1 + 8 * s);
            STAMP(wg, 11 + 4 * s);
            final_tma<true>(base + O_YA + 512 * s, base + O_RV + s * QB, &mp.mo, 16 * cl, 16 * s + 4 * rank, w, lane);
        }
        STAMP(wg, 12);
        wait_bar(bars + B_YB1);
        final_tma<false>(base + O_YB, base + O_RV + 2 * QB, &mp.mo, 448 + 16 * cl, 4 * rank, w, lane);
        KSTAMP(19);
    }
    int wg2;
    asm volatile("mov.u32 %0, %%tid.x;" : "=r"(wg2));
    wg2 >>= 7;
    wait_bar(bars + (wg2 == 2 ? B_YB2 : B_YB3));
    STAMP(wg, 13);
    final_pass(base + O_YB, prm.out + (size_t)(2 * rank) * 896 + 448 + 16 * cl, wg2 == 2 ? 16 + w : 24 + 4 * wg2 + w, wg2 == 2 ? 24 : 28 + 4 * wg2, lane);
    asm volatile("cp.async.bulk.wait_group.read 0;" ::: "memory");
    STAMP(wg, 14);
    TSFLUSH(blockIdx.x);
}

__global__ void __launch_bounds__(128 * HELP_WG, 1) helper_kernel(const __grid_constant__ Params prm) {
    extern __shared__ __align__(1024) char smem[];
    const uint32_t base = (uint32_t)__cvta_generic_to_shared(smem);
    KParams kp;
    {
        const int ch = 4 * min((threadIdx.x >> 7) * NHELP + blockIdx.x, 111u) + 3;
        const size_t po = (size_t)ch * 256 + (threadIdx.x & 127) * 2;
        uint16_t a, b;
        asm volatile("ld.volatile.global.u16 %0, [%1];" : "=h"(a) : "l"(pptr(prm, 6) + ch) : "memory");
#pragma unroll
        for (int i = 0; i < 6; i++) asm volatile("ld.volatile.global.u32 %0, [%1];" : "=r"(kp.p[i]) : "l"(pptr(prm, i) + po) : "memory");
        kp.ldt = a;
        asm volatile("ld.volatile.global.u16 %0, [%1];" : "=h"(b) : "l"(pptr(prm, 7) + ch) : "memory");
        kp.dsk = b;
    }
    const int grp = __shfl_sync(0xffffffff, threadIdx.x >> 7, 0);
    const int tid = threadIdx.x & 127;
    const int hi = grp * NHELP + blockIdx.x;
    TSINIT(HELP_WG * TBL, 0)
    if (hi < 112) {
        unsigned tag = *(volatile unsigned*)&prm.cnt[112 + hi];
        uint32_t o[6];
        const int w = __shfl_sync(0xffffffff, tid >> 5, 0);
        kgen<false>(kp, base + grp * TBL, w, tid & 31, [] {} TSPASS);
        kfinish(base + grp * TBL, w, tid & 31, 1 + grp, o TSPASS);
        tag++;
        if (tid == 0) prm.cnt[112 + hi] = tag;
#pragma unroll
        for (int i = 0; i < 2; i++)
            asm volatile("{ .reg .b128 v; .reg .b64 l, h; mov.b64 l, {%0, %1}; mov.b64 h, {%2, %3}; mov.b128 v, {l, h}; st.relaxed.gpu.global.b128 [%4], v; }"
                         ::"r"(o[3 * i]), "r"(o[3 * i + 1]), "r"(o[3 * i + 2]), "r"(tag), "l"(prm.pkt + hi * 256 + 128 * i + tid) : "memory");
        STAMP(0, 23);
        TSFLUSH(112 + blockIdx.x);
    }
}

typedef CUresult (*EncodeFn)(CUtensorMap*, CUtensorMapDataType, cuuint32_t, void*, const cuuint64_t*, const cuuint64_t*, const cuuint32_t*, const cuuint32_t*,
                             CUtensorMapInterleave, CUtensorMapSwizzle, CUtensorMapL2promotion, CUtensorMapFloatOOBfill);

}

static void launch_on(void* const* d_in, void* d_out, cudaStream_t st) {
    static EncodeFn enc = nullptr;
    static void *pkt = nullptr, *cnt = nullptr;
    if (!enc) {
        cudaDriverEntryPointQueryResult qr;
        cudaGetDriverEntryPoint("cuTensorMapEncodeTiled", (void**)&enc, cudaEnableDefault, &qr);
        cudaGetSymbolAddress(&pkt, g_pkt);
        cudaGetSymbolAddress(&cnt, g_cnt);
        cudaFuncSetAttribute(fused_kernel, cudaFuncAttributeMaxDynamicSharedMemorySize, SMEM_BYTES);
        cudaFuncSetAttribute(helper_kernel, cudaFuncAttributeMaxDynamicSharedMemorySize, HELP_SMEM);
    }
    Params p;
    Maps mp;
    CUtensorMap* maps[5] = {&mp.mk, &mp.mv, &mp.mu, &mp.mq, &mp.mo};
    void* ptrs[5] = {d_in[1], d_in[2], d_in[6], d_in[0], d_out};
    for (int i = 0; i < 5; i++) {
        const cuuint64_t rb = i < 4 ? 896 : 1792;
        cuuint64_t gd[4] = {rb / 2, i < 3 ? 256u : 8u, 8, 32}, gs[3] = {8 * rb, rb, 64 * rb};
        cuuint32_t bx[4] = {16, i == 0 ? 68u : i < 3 ? 64u : 9u, 8, i == 3 ? 4u : 1u}, es[4] = {1, 1, 1, 1};
        enc(maps[i], CU_TENSOR_MAP_DATA_TYPE_BFLOAT16, i < 3 ? 3 : 4, ptrs[i], gd, gs, bx, es, CU_TENSOR_MAP_INTERLEAVE_NONE, i < 3 ? CU_TENSOR_MAP_SWIZZLE_32B : CU_TENSOR_MAP_SWIZZLE_NONE,
            CU_TENSOR_MAP_L2_PROMOTION_NONE, CU_TENSOR_MAP_FLOAT_OOB_FILL_NONE);
    }
    const __nv_bfloat16* const* q = (const __nv_bfloat16* const*)d_in;
    p.shift_k = q[3]; p.ssm_k = q[4]; p.ssm_D = q[5];
    for (int i = 0; i < 8; i++) p.lo[i] = (uint32_t)(uintptr_t)q[7 + i];
    for (int i = 0; i < 4; i++) p.hi[i] = (uint32_t)(((uintptr_t)q[7 + 2 * i] >> 32) & 0xffff) | (uint32_t)((uintptr_t)q[8 + 2 * i] >> 32) << 16;
    p.out = (__nv_bfloat16*)d_out;
    p.pkt = (uint4*)pkt; p.cnt = (unsigned*)cnt;
    fused_kernel<<<112, 384, SMEM_BYTES, st>>>(p, mp);
    cudaLaunchConfig_t cfg = {};
    cfg.gridDim = dim3(NHELP); cfg.blockDim = dim3(128 * HELP_WG); cfg.dynamicSmemBytes = HELP_SMEM; cfg.stream = st;
    cudaLaunchAttribute at[1];
    at[0].id = cudaLaunchAttributeProgrammaticStreamSerialization; at[0].val.programmaticStreamSerializationAllowed = 1;
    cfg.attrs = at; cfg.numAttrs = 1;
    cudaLaunchKernelEx(&cfg, helper_kernel, p);
}

extern "C" void kernel_launch(void* const* d_in, const int* in_sizes, int n_in, void* d_out, int out_size) {
    launch_on(d_in, d_out, cudaStreamPerThread);
}
```
